```python
import torch

def _softmax(x, axis=-1):
    return torch.softmax(x, dim=axis)

def _gelu(x):
    return torch.nn.functional.gelu(x, approximate='tanh')

def _silu(x):
    return torch.nn.functional.silu(x)

def _sigmoid(x):
    return torch.sigmoid(x)

def _layernorm(x, axis=-1, eps=1e-05):
    m = x.mean(dim=axis, keepdim=True)
    v = x.var(dim=axis, keepdim=True, unbiased=False)
    return (x - m) / torch.sqrt(v + eps)

def _scatter_add(tgt, idx, src, axis=0):
    return tgt.clone().index_add_(axis, idx, src)

def _segment_sum(src, seg, n):
    out = torch.zeros((n,) + src.shape[1:], dtype=src.dtype)
    return out.index_add_(0, seg, src)

def _pad(x, pw):
    flat = tuple((v for pair in reversed(pw) for v in pair))
    return torch.nn.functional.pad(x, flat)
kernel_name = 'adaLN_cond__gqa_block_cached__swiglu_ffn__prompt'

def setup_inputs():

    _w = lambda a: (lambda t: t.to(torch.bfloat16) if t.is_floating_point() else t)(torch.as_tensor(a))

    def _A_setup():
        B, Sq, D = (1, 2048, 512)
        Hq, Hkv, Sk, Dh = (32, 8, 2048, 128)
        assert Hq % Hkv == 0, (Hq, Hkv)
        return {'x': _w((lambda *s: torch.randn(*s, dtype=torch.bfloat16) * 0.05)(B, Sq, D)), 'k_cache': _w((lambda *s: torch.randn(*s, dtype=torch.bfloat16) * 3.2)(B, Hkv, Sk, Dh)), 'v_cache': _w((lambda *s: torch.randn(*s, dtype=torch.bfloat16) * 0.4)(B, Hkv, Sk, Dh)), 'wq': _w((lambda *s: torch.randn(*s, dtype=torch.bfloat16) * 3.2)(D, Hq * Dh) * D ** (-0.5)), 'wo': _w((lambda *s: torch.randn(*s, dtype=torch.bfloat16) * 0.4)(Hq * Dh, D) * (Hq * Dh) ** (-0.5))}
    _A_in = _A_setup()

    def _B_setup():
        B, S, D, F = (1, 2048, 512, 1792)
        return {'x': _w((lambda *s: torch.randn(*s, dtype=torch.bfloat16) * 0.05)(B, S, D)), 'w_gate': _w((lambda *s: torch.randn(*s, dtype=torch.bfloat16) * 0.05)(D, F)), 'w_up': _w((lambda *s: torch.randn(*s, dtype=torch.bfloat16) * 0.05)(D, F)), 'w_down': _w((lambda *s: torch.randn(*s, dtype=torch.bfloat16) * 0.05)(F, D))}
    _B_in = _B_setup()
    return {'A_x': _A_in['x'], 'A_k_cache': _A_in['k_cache'], 'A_v_cache': _A_in['v_cache'], 'A_wq': _A_in['wq'], 'A_wo': _A_in['wo'], 'B_x': _B_in['x'], 'B_w_gate': _B_in['w_gate'], 'B_w_up': _B_in['w_up'], 'B_w_down': _B_in['w_down'], 'c': _w((lambda *s: torch.randn(*s, dtype=torch.bfloat16) * 0.1)(1, 512) * 8.0), 'w_mod': _w((lambda *s: torch.randn(*s, dtype=torch.bfloat16) * 0.1)(512, 6 * 512) * 512 ** (-0.5) * 8.0)}

def reference(A_x, A_k_cache, A_v_cache, A_wq, A_wo, B_x, B_w_gate, B_w_up, B_w_down, c, w_mod):

    def _A_ref(x, k_cache, v_cache, wq, wo):
        B, Sq, D = x.shape
        Hq, Dh = (32, 128)
        Hkv = k_cache.shape[1]
        rep = Hq // Hkv
        q = (lambda x, *d: x.permute(*d))((x @ wq).reshape(B, Sq, Hq, Dh), 0, 2, 1, 3)
        k = (lambda x, n, axis: torch.repeat_interleave(x, n, dim=axis))(k_cache, rep, axis=1)
        v = (lambda x, n, axis: torch.repeat_interleave(x, n, dim=axis))(v_cache, rep, axis=1)
        scores = torch.einsum('bhqd,bhkd->bhqk', q, k) * Dh ** (-0.5)
        p = _softmax(scores, axis=-1)
        o = torch.einsum('bhqk,bhkd->bhqd', p, v)
        return (lambda x, *d: x.permute(*d))(o, 0, 2, 1, 3).reshape(B, Sq, Hq * Dh) @ wo

    def _B_ref(x, w_gate, w_up, w_down):
        g = _silu(x @ w_gate)
        u = x @ w_up
        return g * u @ w_down
    x = A_x
    mod = (_silu(c) @ w_mod).reshape(c.shape[0], 6, 1, -1)
    sa, ca, ga, sb, cb, gb = (mod[:, 0].clone(), mod[:, 1].clone(), mod[:, 2].clone(), mod[:, 3].clone(), mod[:, 4].clone(), mod[:, 5].clone())
    h = _layernorm(x, axis=-1) * (1 + ca) + sa
    x = x + ga * _A_ref(h, A_k_cache, A_v_cache, A_wq, A_wo)
    h = _layernorm(x, axis=-1) * (1 + cb) + sb
    x = x + gb * _B_ref(h, B_w_gate, B_w_up, B_w_down)
    return x
```

```cpp
#include <cuda_runtime.h>
#include <cuda_bf16.h>
#include <cuda.h>
#include <stdint.h>

namespace {

constexpr int SEQ = 2048, DM = 512, DH = 128, FF = 1792, FS = 224;
constexpr int SLOT = 32768;
constexpr int OFF_BAR = 7 * SLOT;
constexpr int OFF_MODSM = OFF_BAR + 128;
constexpr int OFF_RED = OFF_MODSM + 2048;
constexpr int OFF_RED2 = OFF_RED + 256;
constexpr int OFF_EPOCH = OFF_RED2 + 192;
constexpr int SMEM_BYTES = 232448;
static_assert(OFF_EPOCH + 16 <= SMEM_BYTES, "smem");
constexpr int STG_PITCH = 1040;

constexpr int CONS_REGS = 232, PROD_REGS = 40;

__device__ uint4 g_part[16 * 8 * 8 * 1024];
__device__ __nv_bfloat16 g_h2[SEQ * DM];
__device__ unsigned long long g_modll[1536];
__device__ unsigned int g_cnt[3 * 16 * 32];
__device__ unsigned int g_epoch;

struct Maps { CUtensorMap wq, k, v, wo, wg, wu, wd, h2; };

__device__ __forceinline__ uint32_t smem_u32(const void* p) { return (uint32_t)__cvta_generic_to_shared(p); }
__device__ __forceinline__ void mbar_init(uint32_t bar, uint32_t cnt) { asm volatile("mbarrier.init.shared::cta.b64 [%0], %1;" :: "r"(bar), "r"(cnt) : "memory"); }
__device__ __forceinline__ void mbar_expect_tx(uint32_t bar, uint32_t bytes) { asm volatile("mbarrier.arrive.expect_tx.shared::cta.b64 _, [%0], %1;" :: "r"(bar), "r"(bytes) : "memory"); }
__device__ __forceinline__ void mbar_arrive_cluster(uint32_t bar, uint32_t cta) {
  asm volatile("{\n.reg .b32 ra;\nmapa.shared::cluster.u32 ra, %0, %1;\nmbarrier.arrive.shared::cluster.b64 _, [ra];\n}" :: "r"(bar), "r"(cta) : "memory");
}
__device__ __forceinline__ void mbar_wait(uint32_t bar, uint32_t par) {
  asm volatile(
    "{\n.reg .pred p;\n.reg .u32 n;\n"
    "mbarrier.try_wait.parity.shared::cta.b64 p, [%0], %1;\n"
    "@p bra W_DONE;\n"
    "mov.u32 n, 0;\n"
    "W_LOOP:\n"
    "mbarrier.try_wait.parity.shared::cta.b64 p, [%0], %1;\n"
    "@p bra W_DONE;\n"
    "add.u32 n, n, 1;\n"
    "setp.lt.u32 p, n, 0x1000000;\n"
    "@p bra W_LOOP;\n"
    "trap;\n"
    "W_DONE:\n}" :: "r"(bar), "r"(par) : "memory");
}
__device__ __forceinline__ void tma_load(uint32_t dst, const CUtensorMap* m, uint32_t bar, int c0, int c1) {
  asm volatile("cp.async.bulk.tensor.2d.shared::cluster.global.mbarrier::complete_tx::bytes [%0], [%1, {%3, %4}], [%2];" :: "r"(dst), "l"(m), "r"(bar), "r"(c0), "r"(c1) : "memory");
}
__device__ __forceinline__ void tma_load_mc(uint32_t dst, const CUtensorMap* m, uint32_t bar, int c0, int c1) {
  asm volatile("cp.async.bulk.tensor.2d.shared::cluster.global.mbarrier::complete_tx::bytes.multicast::cluster [%0], [%1, {%3, %4}], [%2], %5;" :: "r"(dst), "l"(m), "r"(bar), "r"(c0), "r"(c1), "h"((uint16_t)3) : "memory");
}
__device__ __forceinline__ void tma_prefetch(const CUtensorMap* m, int c0, int c1) {
  asm volatile("cp.async.bulk.prefetch.tensor.2d.L2.global [%0, {%1, %2}];" :: "l"(m), "r"(c0), "r"(c1) : "memory");
}
__device__ __forceinline__ void bulk_prefetch(const void* p, uint32_t bytes) {
  asm volatile("cp.async.bulk.prefetch.L2.global [%0], %1;" :: "l"(p), "r"(bytes) : "memory");
}
__device__ __forceinline__ void bulk_store(void* dst, uint32_t src, uint32_t bytes) {
  asm volatile("cp.async.bulk.global.shared::cta.bulk_group [%0], [%1], %2;" :: "l"(dst), "r"(src), "r"(bytes) : "memory");
}
__device__ __forceinline__ void desc_prefetch(const CUtensorMap* m) { asm volatile("prefetch.tensormap [%0];" :: "l"(m) : "memory"); }
__device__ __forceinline__ void fence_async_smem() { asm volatile("fence.proxy.async.shared::cta;" ::: "memory"); }
__device__ __forceinline__ void fence_async_all() { asm volatile("fence.proxy.async;" ::: "memory"); }
__device__ __forceinline__ void fence_gpu() { asm volatile("fence.acq_rel.gpu;" ::: "memory"); }
__device__ __forceinline__ void bar_sync(int id, int n) { asm volatile("bar.sync %0, %1;" :: "r"(id), "r"(n) : "memory"); }
__device__ __forceinline__ void bar_arrive(int id, int n) { asm volatile("bar.arrive %0, %1;" :: "r"(id), "r"(n) : "memory"); }
__device__ __forceinline__ void wg_fence() { asm volatile("wgmma.fence.sync.aligned;" ::: "memory"); }
__device__ __forceinline__ void wg_commit() { asm volatile("wgmma.commit_group.sync.aligned;" ::: "memory"); }
template <int N> __device__ __forceinline__ void wg_wait() { asm volatile("wgmma.wait_group.sync.aligned %0;" :: "n"(N) : "memory"); }
template <int N> __device__ __forceinline__ void pin(float (&r)[N]) {
#pragma unroll
  for (int i = 0; i < N; i++) asm volatile("" : "+f"(r[i]) :: "memory");
}
template <int N> __device__ __forceinline__ void pin(uint32_t (&r)[N]) {
#pragma unroll
  for (int i = 0; i < N; i++) asm volatile("" : "+r"(r[i]) :: "memory");
}
__device__ __forceinline__ uint64_t make_desc(uint32_t addr, uint32_t lbo, uint32_t sbo) {
  return (uint64_t)((addr & 0x3FFFF) >> 4) | ((uint64_t)(lbo >> 4) << 16) | ((uint64_t)(sbo >> 4) << 32) | (1ull << 62);
}
__device__ __forceinline__ float ex2(float x) { float y; asm("ex2.approx.ftz.f32 %0, %1;" : "=f"(y) : "f"(x)); return y; }
__device__ __forceinline__ float tanh_fast(float x) { float y; asm("tanh.approx.f32 %0, %1;" : "=f"(y) : "f"(x)); return y; }
__device__ __forceinline__ uint32_t pack2(float lo, float hi) { uint32_t r; asm("cvt.rn.bf16x2.f32 %0, %1, %2;" : "=r"(r) : "f"(hi), "f"(lo)); return r; }
__device__ __forceinline__ float blo(uint32_t w) { return __uint_as_float(w << 16); }
__device__ __forceinline__ float bhi(uint32_t w) { return __uint_as_float(w & 0xffff0000u); }
__device__ __forceinline__ float bround(float x) { return blo(pack2(x, 0.f)); }
__device__ __forceinline__ uint32_t hfma2(uint32_t a, uint32_t b, uint32_t c) { uint32_t r; asm("fma.rn.bf16x2 %0, %1, %2, %3;" : "=r"(r) : "r"(a), "r"(b), "r"(c)); return r; }
__device__ __forceinline__ uint32_t one_plus(uint32_t w) { return pack2(1.f + blo(w), 1.f + bhi(w)); }
__device__ __forceinline__ void ldsm4(uint32_t addr, uint32_t& a, uint32_t& b, uint32_t& c, uint32_t& d) {
  asm volatile("ldmatrix.sync.aligned.m8n8.x4.shared.b16 {%0,%1,%2,%3}, [%4];" : "=r"(a), "=r"(b), "=r"(c), "=r"(d) : "r"(addr) : "memory");
}
__device__ __forceinline__ void stsm4(uint32_t addr, uint32_t a, uint32_t b, uint32_t c, uint32_t d) {
  asm volatile("stmatrix.sync.aligned.m8n8.x4.shared.b16 [%0], {%1,%2,%3,%4};" :: "r"(addr), "r"(a), "r"(b), "r"(c), "r"(d) : "memory");
}
__device__ __forceinline__ void sts128(uint32_t addr, uint32_t a, uint32_t b, uint32_t c, uint32_t d) {
  asm volatile("st.shared.v4.b32 [%0], {%1,%2,%3,%4};" :: "r"(addr), "r"(a), "r"(b), "r"(c), "r"(d) : "memory");
}
__device__ __forceinline__ uint4 lds128(uint32_t addr) {
  uint4 v; asm volatile("ld.shared.v4.b32 {%0,%1,%2,%3}, [%4];" : "=r"(v.x), "=r"(v.y), "=r"(v.z), "=r"(v.w) : "r"(addr) : "memory"); return v;
}
__device__ __forceinline__ void sts32(uint32_t addr, uint32_t v) { asm volatile("st.shared.b32 [%0], %1;" :: "r"(addr), "r"(v) : "memory"); }
__device__ __forceinline__ uint32_t lds32(uint32_t addr) { uint32_t v; asm volatile("ld.shared.b32 %0, [%1];" : "=r"(v) : "r"(addr) : "memory"); return v; }
__device__ __forceinline__ uint4 ldg_nc128(const void* p) {
  uint4 v; asm volatile("ld.global.nc.v4.b32 {%0,%1,%2,%3}, [%4];" : "=r"(v.x), "=r"(v.y), "=r"(v.z), "=r"(v.w) : "l"(p)); return v;
}
__device__ __forceinline__ uint4 ldg_cg128(const void* p) {
  uint4 v; asm volatile("ld.global.cg.v4.b32 {%0,%1,%2,%3}, [%4];" : "=r"(v.x), "=r"(v.y), "=r"(v.z), "=r"(v.w) : "l"(p) : "memory"); return v;
}
__device__ __forceinline__ uint32_t ldg_nc32(const void* p) { uint32_t v; asm volatile("ld.global.nc.b32 %0, [%1];" : "=r"(v) : "l"(p)); return v; }
__device__ __forceinline__ void stg128(void* p, uint32_t a, uint32_t b, uint32_t c, uint32_t d) {
  asm volatile("st.global.v4.b32 [%0], {%1,%2,%3,%4};" :: "l"(p), "r"(a), "r"(b), "r"(c), "r"(d) : "memory");
}
__device__ __forceinline__ unsigned long long ld_ll(const unsigned long long* p) {
  unsigned long long v; asm volatile("ld.relaxed.gpu.global.b64 %0, [%1];" : "=l"(v) : "l"(p) : "memory"); return v;
}
__device__ __forceinline__ void st_ll(unsigned long long* p, uint32_t val, uint32_t tag) {
  asm volatile("st.relaxed.gpu.global.b64 [%0], %1;" :: "l"(p), "l"(((unsigned long long)tag << 32) | val) : "memory");
}
__device__ __forceinline__ uint32_t get_ll(const unsigned long long* p, unsigned long long v, uint32_t tag) {
  uint32_t r;
  asm volatile(
    "{\n.reg .pred p;\n.reg .u32 n, t;\n.reg .b64 v;\n"
    "mov.b64 {%0, t}, %2;\n"
    "setp.eq.u32 p, t, %3;\n"
    "@p bra L_DONE;\n"
    "mov.u32 n, 0;\n"
    "L_LOOP:\n"
    "ld.relaxed.gpu.global.b64 v, [%1];\n"
    "mov.b64 {%0, t}, v;\n"
    "setp.eq.u32 p, t, %3;\n"
    "@p bra L_DONE;\n"
    "add.u32 n, n, 1;\n"
    "setp.lt.u32 p, n, 0x1000000;\n"
    "@p bra L_LOOP;\n"
    "trap;\n"
    "L_DONE:\n}" : "=&r"(r) : "l"(p), "l"(v), "r"(tag) : "memory");
  return r;
}
__device__ __forceinline__ void cnt_signal(unsigned int* c) { asm volatile("red.release.gpu.global.add.u32 [%0], 1;" :: "l"(c) : "memory"); }
__device__ __forceinline__ void cnt_wait(const unsigned int* c, uint32_t target) {
  asm volatile(
    "{\n.reg .pred p;\n.reg .u32 n, x;\n"
    "mov.u32 n, 0;\n"
    "C_LOOP:\n"
    "ld.acquire.gpu.global.u32 x, [%0];\n"
    "sub.u32 x, x, %1;\n"
    "setp.ge.s32 p, x, 0;\n"
    "@p bra C_DONE;\n"
    "add.u32 n, n, 1;\n"
    "setp.lt.u32 p, n, 0x1000000;\n"
    "@p bra C_LOOP;\n"
    "trap;\n"
    "C_DONE:\n}" :: "l"(c), "r"(target) : "memory");
}
__device__ __forceinline__ float silu_bf(float x) { return bround(x / (1.f + __expf(-x))); }
__device__ __forceinline__ void mma16816(float& c0, float& c1, float& c2, float& c3, uint32_t a0, uint32_t a1, uint32_t a2, uint32_t a3, uint32_t b0, uint32_t b1) {
  asm("mma.sync.aligned.m16n8k16.row.col.f32.bf16.bf16.f32 {%0,%1,%2,%3}, {%4,%5,%6,%7}, {%8,%9}, {%0,%1,%2,%3};"
      : "+f"(c0), "+f"(c1), "+f"(c2), "+f"(c3) : "r"(a0), "r"(a1), "r"(a2), "r"(a3), "r"(b0), "r"(b1));
}

template <int O, int N> __device__ __forceinline__ void xreduce(float (&v)[N], int lane) {
  const bool up = lane & O;
#pragma unroll
  for (int i = 0; i < O; i++) { const float snd = up ? v[i] : v[i + O], kp = up ? v[i + O] : v[i]; v[i] = kp + __shfl_xor_sync(~0u, snd, O); }
}

__device__ __forceinline__ void wgmma_rs_n128_t0(float (&d)[64], uint32_t a0, uint32_t a1, uint32_t a2, uint32_t a3, uint64_t db, int scale_d) {
  asm volatile(
    "{\n.reg .pred p;\nsetp.ne.b32 p, %69, 0;\n"
    "wgmma.mma_async.sync.aligned.m64n128k16.f32.bf16.bf16 {"
    "%0, %1, %2, %3, %4, %5, %6, %7, %8, %9, %10, %11, %12, %13, %14, %15, "
    "%16, %17, %18, %19, %20, %21, %22, %23, %24, %25, %26, %27, %28, %29, %30, %31, "
    "%32, %33, %34, %35, %36, %37, %38, %39, %40, %41, %42, %43, %44, %45, %46, %47, "
    "%48, %49, %50, %51, %52, %53, %54, %55, %56, %57, %58, %59, %60, %61, %62, %63"
    "}, {%64, %65, %66, %67}, %68, p, 1, 1, 0;\n}\n"
    : "+f"(d[0]), "+f"(d[1]), "+f"(d[2]), "+f"(d[3]), "+f"(d[4]), "+f"(d[5]), "+f"(d[6]), "+f"(d[7]),
      "+f"(d[8]), "+f"(d[9]), "+f"(d[10]), "+f"(d[11]), "+f"(d[12]), "+f"(d[13]), "+f"(d[14]), "+f"(d[15]),
      "+f"(d[16]), "+f"(d[17]), "+f"(d[18]), "+f"(d[19]), "+f"(d[20]), "+f"(d[21]), "+f"(d[22]), "+f"(d[23]),
      "+f"(d[24]), "+f"(d[25]), "+f"(d[26]), "+f"(d[27]), "+f"(d[28]), "+f"(d[29]), "+f"(d[30]), "+f"(d[31]),
      "+f"(d[32]), "+f"(d[33]), "+f"(d[34]), "+f"(d[35]), "+f"(d[36]), "+f"(d[37]), "+f"(d[38]), "+f"(d[39]),
      "+f"(d[40]), "+f"(d[41]), "+f"(d[42]), "+f"(d[43]), "+f"(d[44]), "+f"(d[45]), "+f"(d[46]), "+f"(d[47]),
      "+f"(d[48]), "+f"(d[49]), "+f"(d[50]), "+f"(d[51]), "+f"(d[52]), "+f"(d[53]), "+f"(d[54]), "+f"(d[55]),
      "+f"(d[56]), "+f"(d[57]), "+f"(d[58]), "+f"(d[59]), "+f"(d[60]), "+f"(d[61]), "+f"(d[62]), "+f"(d[63])
    : "r"(a0), "r"(a1), "r"(a2), "r"(a3), "l"(db), "r"(scale_d));
}
__device__ __forceinline__ void wgmma_rs_n128_t1(float (&d)[64], uint32_t a0, uint32_t a1, uint32_t a2, uint32_t a3, uint64_t db, int scale_d) {
  asm volatile(
    "{\n.reg .pred p;\nsetp.ne.b32 p, %69, 0;\n"
    "wgmma.mma_async.sync.aligned.m64n128k16.f32.bf16.bf16 {"
    "%0, %1, %2, %3, %4, %5, %6, %7, %8, %9, %10, %11, %12, %13, %14, %15, "
    "%16, %17, %18, %19, %20, %21, %22, %23, %24, %25, %26, %27, %28, %29, %30, %31, "
    "%32, %33, %34, %35, %36, %37, %38, %39, %40, %41, %42, %43, %44, %45, %46, %47, "
    "%48, %49, %50, %51, %52, %53, %54, %55, %56, %57, %58, %59, %60, %61, %62, %63"
    "}, {%64, %65, %66, %67}, %68, p, 1, 1, 1;\n}\n"
    : "+f"(d[0]), "+f"(d[1]), "+f"(d[2]), "+f"(d[3]), "+f"(d[4]), "+f"(d[5]), "+f"(d[6]), "+f"(d[7]),
      "+f"(d[8]), "+f"(d[9]), "+f"(d[10]), "+f"(d[11]), "+f"(d[12]), "+f"(d[13]), "+f"(d[14]), "+f"(d[15]),
      "+f"(d[16]), "+f"(d[17]), "+f"(d[18]), "+f"(d[19]), "+f"(d[20]), "+f"(d[21]), "+f"(d[22]), "+f"(d[23]),
      "+f"(d[24]), "+f"(d[25]), "+f"(d[26]), "+f"(d[27]), "+f"(d[28]), "+f"(d[29]), "+f"(d[30]), "+f"(d[31]),
      "+f"(d[32]), "+f"(d[33]), "+f"(d[34]), "+f"(d[35]), "+f"(d[36]), "+f"(d[37]), "+f"(d[38]), "+f"(d[39]),
      "+f"(d[40]), "+f"(d[41]), "+f"(d[42]), "+f"(d[43]), "+f"(d[44]), "+f"(d[45]), "+f"(d[46]), "+f"(d[47]),
      "+f"(d[48]), "+f"(d[49]), "+f"(d[50]), "+f"(d[51]), "+f"(d[52]), "+f"(d[53]), "+f"(d[54]), "+f"(d[55]),
      "+f"(d[56]), "+f"(d[57]), "+f"(d[58]), "+f"(d[59]), "+f"(d[60]), "+f"(d[61]), "+f"(d[62]), "+f"(d[63])
    : "r"(a0), "r"(a1), "r"(a2), "r"(a3), "l"(db), "r"(scale_d));
}
__device__ __forceinline__ void wgmma_ss_n256_t1(float (&d)[128], uint64_t da, uint64_t db, int scale_d) {
  asm volatile(
    "{\n.reg .pred p;\nsetp.ne.b32 p, %130, 0;\n"
    "wgmma.mma_async.sync.aligned.m64n256k16.f32.bf16.bf16 {"
    "%0, %1, %2, %3, %4, %5, %6, %7, %8, %9, %10, %11, %12, %13, %14, %15, "
    "%16, %17, %18, %19, %20, %21, %22, %23, %24, %25, %26, %27, %28, %29, %30, %31, "
    "%32, %33, %34, %35, %36, %37, %38, %39, %40, %41, %42, %43, %44, %45, %46, %47, "
    "%48, %49, %50, %51, %52, %53, %54, %55, %56, %57, %58, %59, %60, %61, %62, %63, "
    "%64, %65, %66, %67, %68, %69, %70, %71, %72, %73, %74, %75, %76, %77, %78, %79, "
    "%80, %81, %82, %83, %84, %85, %86, %87, %88, %89, %90, %91, %92, %93, %94, %95, "
    "%96, %97, %98, %99, %100, %101, %102, %103, %104, %105, %106, %107, %108, %109, %110, %111, "
    "%112, %113, %114, %115, %116, %117, %118, %119, %120, %121, %122, %123, %124, %125, %126, %127"
    "}, %128, %129, p, 1, 1, 0, 1;\n}\n"
    : "+f"(d[0]), "+f"(d[1]), "+f"(d[2]), "+f"(d[3]), "+f"(d[4]), "+f"(d[5]), "+f"(d[6]), "+f"(d[7]),
      "+f"(d[8]), "+f"(d[9]), "+f"(d[10]), "+f"(d[11]), "+f"(d[12]), "+f"(d[13]), "+f"(d[14]), "+f"(d[15]),
      "+f"(d[16]), "+f"(d[17]), "+f"(d[18]), "+f"(d[19]), "+f"(d[20]), "+f"(d[21]), "+f"(d[22]), "+f"(d[23]),
      "+f"(d[24]), "+f"(d[25]), "+f"(d[26]), "+f"(d[27]), "+f"(d[28]), "+f"(d[29]), "+f"(d[30]), "+f"(d[31]),
      "+f"(d[32]), "+f"(d[33]), "+f"(d[34]), "+f"(d[35]), "+f"(d[36]), "+f"(d[37]), "+f"(d[38]), "+f"(d[39]),
      "+f"(d[40]), "+f"(d[41]), "+f"(d[42]), "+f"(d[43]), "+f"(d[44]), "+f"(d[45]), "+f"(d[46]), "+f"(d[47]),
      "+f"(d[48]), "+f"(d[49]), "+f"(d[50]), "+f"(d[51]), "+f"(d[52]), "+f"(d[53]), "+f"(d[54]), "+f"(d[55]),
      "+f"(d[56]), "+f"(d[57]), "+f"(d[58]), "+f"(d[59]), "+f"(d[60]), "+f"(d[61]), "+f"(d[62]), "+f"(d[63]),
      "+f"(d[64]), "+f"(d[65]), "+f"(d[66]), "+f"(d[67]), "+f"(d[68]), "+f"(d[69]), "+f"(d[70]), "+f"(d[71]),
      "+f"(d[72]), "+f"(d[73]), "+f"(d[74]), "+f"(d[75]), "+f"(d[76]), "+f"(d[77]), "+f"(d[78]), "+f"(d[79]),
      "+f"(d[80]), "+f"(d[81]), "+f"(d[82]), "+f"(d[83]), "+f"(d[84]), "+f"(d[85]), "+f"(d[86]), "+f"(d[87]),
      "+f"(d[88]), "+f"(d[89]), "+f"(d[90]), "+f"(d[91]), "+f"(d[92]), "+f"(d[93]), "+f"(d[94]), "+f"(d[95]),
      "+f"(d[96]), "+f"(d[97]), "+f"(d[98]), "+f"(d[99]), "+f"(d[100]), "+f"(d[101]), "+f"(d[102]), "+f"(d[103]),
      "+f"(d[104]), "+f"(d[105]), "+f"(d[106]), "+f"(d[107]), "+f"(d[108]), "+f"(d[109]), "+f"(d[110]), "+f"(d[111]),
      "+f"(d[112]), "+f"(d[113]), "+f"(d[114]), "+f"(d[115]), "+f"(d[116]), "+f"(d[117]), "+f"(d[118]), "+f"(d[119]),
      "+f"(d[120]), "+f"(d[121]), "+f"(d[122]), "+f"(d[123]), "+f"(d[124]), "+f"(d[125]), "+f"(d[126]), "+f"(d[127])
    : "l"(da), "l"(db), "r"(scale_d));
}
__device__ __forceinline__ void wgmma_rs_n256_t1(float (&d)[128], uint32_t a0, uint32_t a1, uint32_t a2, uint32_t a3, uint64_t db, int scale_d) {
  asm volatile(
    "{\n.reg .pred p;\nsetp.ne.b32 p, %133, 0;\n"
    "wgmma.mma_async.sync.aligned.m64n256k16.f32.bf16.bf16 {"
    "%0, %1, %2, %3, %4, %5, %6, %7, %8, %9, %10, %11, %12, %13, %14, %15, "
    "%16, %17, %18, %19, %20, %21, %22, %23, %24, %25, %26, %27, %28, %29, %30, %31, "
    "%32, %33, %34, %35, %36, %37, %38, %39, %40, %41, %42, %43, %44, %45, %46, %47, "
    "%48, %49, %50, %51, %52, %53, %54, %55, %56, %57, %58, %59, %60, %61, %62, %63, "
    "%64, %65, %66, %67, %68, %69, %70, %71, %72, %73, %74, %75, %76, %77, %78, %79, "
    "%80, %81, %82, %83, %84, %85, %86, %87, %88, %89, %90, %91, %92, %93, %94, %95, "
    "%96, %97, %98, %99, %100, %101, %102, %103, %104, %105, %106, %107, %108, %109, %110, %111, "
    "%112, %113, %114, %115, %116, %117, %118, %119, %120, %121, %122, %123, %124, %125, %126, %127"
    "}, {%128, %129, %130, %131}, %132, p, 1, 1, 1;\n}\n"
    : "+f"(d[0]), "+f"(d[1]), "+f"(d[2]), "+f"(d[3]), "+f"(d[4]), "+f"(d[5]), "+f"(d[6]), "+f"(d[7]),
      "+f"(d[8]), "+f"(d[9]), "+f"(d[10]), "+f"(d[11]), "+f"(d[12]), "+f"(d[13]), "+f"(d[14]), "+f"(d[15]),
      "+f"(d[16]), "+f"(d[17]), "+f"(d[18]), "+f"(d[19]), "+f"(d[20]), "+f"(d[21]), "+f"(d[22]), "+f"(d[23]),
      "+f"(d[24]), "+f"(d[25]), "+f"(d[26]), "+f"(d[27]), "+f"(d[28]), "+f"(d[29]), "+f"(d[30]), "+f"(d[31]),
      "+f"(d[32]), "+f"(d[33]), "+f"(d[34]), "+f"(d[35]), "+f"(d[36]), "+f"(d[37]), "+f"(d[38]), "+f"(d[39]),
      "+f"(d[40]), "+f"(d[41]), "+f"(d[42]), "+f"(d[43]), "+f"(d[44]), "+f"(d[45]), "+f"(d[46]), "+f"(d[47]),
      "+f"(d[48]), "+f"(d[49]), "+f"(d[50]), "+f"(d[51]), "+f"(d[52]), "+f"(d[53]), "+f"(d[54]), "+f"(d[55]),
      "+f"(d[56]), "+f"(d[57]), "+f"(d[58]), "+f"(d[59]), "+f"(d[60]), "+f"(d[61]), "+f"(d[62]), "+f"(d[63]),
      "+f"(d[64]), "+f"(d[65]), "+f"(d[66]), "+f"(d[67]), "+f"(d[68]), "+f"(d[69]), "+f"(d[70]), "+f"(d[71]),
      "+f"(d[72]), "+f"(d[73]), "+f"(d[74]), "+f"(d[75]), "+f"(d[76]), "+f"(d[77]), "+f"(d[78]), "+f"(d[79]),
      "+f"(d[80]), "+f"(d[81]), "+f"(d[82]), "+f"(d[83]), "+f"(d[84]), "+f"(d[85]), "+f"(d[86]), "+f"(d[87]),
      "+f"(d[88]), "+f"(d[89]), "+f"(d[90]), "+f"(d[91]), "+f"(d[92]), "+f"(d[93]), "+f"(d[94]), "+f"(d[95]),
      "+f"(d[96]), "+f"(d[97]), "+f"(d[98]), "+f"(d[99]), "+f"(d[100]), "+f"(d[101]), "+f"(d[102]), "+f"(d[103]),
      "+f"(d[104]), "+f"(d[105]), "+f"(d[106]), "+f"(d[107]), "+f"(d[108]), "+f"(d[109]), "+f"(d[110]), "+f"(d[111]),
      "+f"(d[112]), "+f"(d[113]), "+f"(d[114]), "+f"(d[115]), "+f"(d[116]), "+f"(d[117]), "+f"(d[118]), "+f"(d[119]),
      "+f"(d[120]), "+f"(d[121]), "+f"(d[122]), "+f"(d[123]), "+f"(d[124]), "+f"(d[125]), "+f"(d[126]), "+f"(d[127])
    : "r"(a0), "r"(a1), "r"(a2), "r"(a3), "l"(db), "r"(scale_d));
}
__device__ __forceinline__ void wgmma_ss_n96_t1(float (&d)[48], uint64_t da, uint64_t db, int scale_d) {
  asm volatile(
    "{\n.reg .pred p;\nsetp.ne.b32 p, %50, 0;\n"
    "wgmma.mma_async.sync.aligned.m64n96k16.f32.bf16.bf16 {"
    "%0, %1, %2, %3, %4, %5, %6, %7, %8, %9, %10, %11, %12, %13, %14, %15, "
    "%16, %17, %18, %19, %20, %21, %22, %23, %24, %25, %26, %27, %28, %29, %30, %31, "
    "%32, %33, %34, %35, %36, %37, %38, %39, %40, %41, %42, %43, %44, %45, %46, %47"
    "}, %48, %49, p, 1, 1, 0, 1;\n}\n"
    : "+f"(d[0]), "+f"(d[1]), "+f"(d[2]), "+f"(d[3]), "+f"(d[4]), "+f"(d[5]), "+f"(d[6]), "+f"(d[7]),
      "+f"(d[8]), "+f"(d[9]), "+f"(d[10]), "+f"(d[11]), "+f"(d[12]), "+f"(d[13]), "+f"(d[14]), "+f"(d[15]),
      "+f"(d[16]), "+f"(d[17]), "+f"(d[18]), "+f"(d[19]), "+f"(d[20]), "+f"(d[21]), "+f"(d[22]), "+f"(d[23]),
      "+f"(d[24]), "+f"(d[25]), "+f"(d[26]), "+f"(d[27]), "+f"(d[28]), "+f"(d[29]), "+f"(d[30]), "+f"(d[31]),
      "+f"(d[32]), "+f"(d[33]), "+f"(d[34]), "+f"(d[35]), "+f"(d[36]), "+f"(d[37]), "+f"(d[38]), "+f"(d[39]),
      "+f"(d[40]), "+f"(d[41]), "+f"(d[42]), "+f"(d[43]), "+f"(d[44]), "+f"(d[45]), "+f"(d[46]), "+f"(d[47])
    : "l"(da), "l"(db), "r"(scale_d));
}

#define TS(k)

constexpr int B_PP = 1;
constexpr int B_CONS = 3;
constexpr int B_WG = 4;
constexpr int B_AUX = 6;

__global__ void __cluster_dims__(2, 1, 1) __launch_bounds__(384, 1)
fused_kernel(const __grid_constant__ Maps mp, const __nv_bfloat16* __restrict__ x, const __nv_bfloat16* __restrict__ kc,
             const __nv_bfloat16* __restrict__ wo, const __nv_bfloat16* __restrict__ wg, const __nv_bfloat16* __restrict__ wu,
             const __nv_bfloat16* __restrict__ wd, const __nv_bfloat16* __restrict__ cvec, const __nv_bfloat16* __restrict__ wmod,
             __nv_bfloat16* __restrict__ out) {
  extern __shared__ __align__(1024) uint8_t sm_raw[];
  const uint32_t sb = smem_u32(sm_raw);
  const int tid = threadIdx.x, lane = tid & 31;
  const int b = blockIdx.x;
  const uint32_t rank = b & 1;
  const int g = (b >> 1) & 7;
  const int rt = (b >> 4) * 2 + rank;
  auto FULL = [&](int s) { return sb + OFF_BAR + 8 * s; };
  auto EMPTY = [&](int s) { return sb + OFF_BAR + 56 + 8 * s; };

  if (tid == 0) {
    asm volatile("{\n.reg .pred p;\nsetp.ne.u32 p, %0, 0;\n@p trap;\n}" :: "r"(sb & 1023));
    for (int s = 0; s < 7; s++) { mbar_init(FULL(s), 1); mbar_init(EMPTY(s), 16); }
    asm volatile("fence.mbarrier_init.release.cluster;" ::: "memory");
  }
  __syncwarp();
  asm volatile("barrier.cluster.arrive.relaxed.aligned;" ::: "memory");

  if (tid < 128) {
    asm volatile("setmaxnreg.dec.sync.aligned.u32 %0;" :: "n"(PROD_REGS));
    asm volatile("barrier.cluster.wait.aligned;" ::: "memory");
    if (tid == 0) {
      uint32_t pe = 0x70;
      auto acquire = [&](int s) { mbar_wait(EMPTY(s), (pe >> s) & 1); pe ^= 1u << s; mbar_expect_tx(FULL(s), SLOT); };
      auto load4 = [&](int s, const CUtensorMap* m, int xx, int yy) {
        tma_load_mc(sb + s * SLOT + rank * 16384, m, FULL(s), xx, yy);
        tma_load_mc(sb + s * SLOT + rank * 16384 + 8192, m, FULL(s), xx + 64, yy);
      };
      int s3 = 4;
      for (int i = 0; i < 16; i++) {
        acquire(s3);
        load4(s3, &mp.wq, g * 512 + (i < 8 ? 256 : 0) + rank * 128, (i & 7) * 64);
        s3 = s3 == 6 ? 4 : s3 + 1;
        if (i == 2) {
          for (int j = 0; j < 4; j++) tma_prefetch(&mp.wq, g * 512 + (rt < 8 ? 256 : 0) + j * 64, (rt & 7) * 64);
          desc_prefetch(&mp.k); desc_prefetch(&mp.v);
        }
        if (i == 3) {
          tma_prefetch(&mp.k, 0, g * SEQ + rt * 128); tma_prefetch(&mp.k, 64, g * SEQ + rt * 128);
          tma_prefetch(&mp.v, 0, g * SEQ + rt * 128); tma_prefetch(&mp.v, 64, g * SEQ + rt * 128);
        }
      }
      for (int t = 0; t <= 64; t++) {
        if (t < 64) { const int s = 5 + (t & 1); acquire(s); tma_load_mc(sb + s * SLOT + rank * 16384, &mp.k, FULL(s), rank * 64, g * SEQ + (t & 15) * 128); }
        if (t > 0) { const int s = 3 + (t & 1); acquire(s); tma_load_mc(sb + s * SLOT + rank * 16384, &mp.v, FULL(s), rank * 64, g * SEQ + ((t - 1) & 15) * 128); }
      }
      for (int i = 0; i < 16; i++) {
        const int s = (0x3465 >> ((i & 3) * 4)) & 7;
        acquire(s);
        load4(s, &mp.wo, (i >> 3) * 256 + rank * 128, g * 512 + (i & 7) * 64);
      }
      s3 = 5;
      for (int i = 0; i < 24; i++) {
        acquire(s3);
        if (i < 16) load4(s3, rank ? &mp.wu : &mp.wg, g * FS + (i >> 3) * 128, (i & 7) * 64);
        else load4(s3, &mp.wd, ((i - 16) >> 2) * 256 + rank * 128, g * FS + (i & 3) * 64);
        s3 = s3 == 6 ? 4 : s3 + 1;
        if (i == 2) {
          const uint32_t tag = lds32(sb + OFF_EPOCH);
          cnt_wait(&g_cnt[(16 + rt) * 32], tag * 8);
          fence_async_all();
          for (int s = 0; s < 4; s++) {
            mbar_expect_tx(FULL(s), SLOT);
            tma_load(sb + s * SLOT, &mp.h2, FULL(s), s * 128, rt * 128);
            tma_load(sb + s * SLOT + 16384, &mp.h2, FULL(s), s * 128 + 64, rt * 128);
          }
        }
      }
    } else if (tid >= 32) {
      const int j = tid - 32;
      mbar_wait(FULL(3), 0);
      if (j == 0) {
        bulk_prefetch((const uint8_t*)wo + (size_t)b * 32768, 32768);
        bulk_prefetch((const uint8_t*)wg + (size_t)b * 14336, 14336);
        bulk_prefetch((const uint8_t*)wu + (size_t)b * 14336, 14336);
        bulk_prefetch((const uint8_t*)wd + (size_t)b * 14336, 14336);
      }
      float a[8];
#pragma unroll
      for (int i = 0; i < 8; i++) a[i] = 0.f;
#pragma unroll 2
      for (int k = j >> 1; k < 512; k += 48) {
        const uint4 w = ldg_nc128(wmod + (size_t)k * 3072 + 1024 + b * 16 + (j & 1) * 8);
        const float sc = silu_bf(__bfloat162float(cvec[k]));
        a[0] += sc * blo(w.x); a[1] += sc * bhi(w.x); a[2] += sc * blo(w.y); a[3] += sc * bhi(w.y);
        a[4] += sc * blo(w.z); a[5] += sc * bhi(w.z); a[6] += sc * blo(w.w); a[7] += sc * bhi(w.w);
      }
#pragma unroll
      for (int i = 0; i < 8; i++) {
#pragma unroll
        for (int o = 2; o < 32; o <<= 1) a[i] += __shfl_xor_sync(~0u, a[i], o);
      }
      if (lane < 2) {
#pragma unroll
        for (int i = 0; i < 8; i++) sts32(sb + OFF_RED2 + ((j >> 5) * 16 + lane * 8 + i) * 4, __float_as_uint(a[i]));
      }
      bar_sync(B_AUX, 96);
      if (j < 8) {
        float v0 = 0.f, v1 = 0.f;
#pragma unroll
        for (int w = 0; w < 3; w++) { v0 += __uint_as_float(lds32(sb + OFF_RED2 + (w * 16 + 2 * j) * 4)); v1 += __uint_as_float(lds32(sb + OFF_RED2 + (w * 16 + 2 * j + 1) * 4)); }
        st_ll(&g_modll[512 + b * 8 + j], pack2(v0, v1), lds32(sb + OFF_EPOCH));
      }
    }
  } else {
    asm volatile("setmaxnreg.inc.sync.aligned.u32 %0;" :: "n"(CONS_REGS));
    const int ct = tid - 128, cw = ct >> 7, wid = ct >> 5;
    auto release = [&](int s) { if (lane < 2) mbar_arrive_cluster(EMPTY(s), lane); };
    const uint32_t frag_row = wid * 16 + (lane & 15);
    auto frag_addr = [&](int slot, int kk) { return sb + slot * SLOT + (kk >> 2) * 16384 + frag_row * 128 + ((((kk & 3) * 2 + (lane >> 4)) ^ (lane & 7)) << 4); };
    uint32_t tag;

    {
      asm volatile("ld.relaxed.gpu.global.u32 %0, [%1];" : "=r"(tag) : "l"(&g_epoch) : "memory");
      const uint4 w0 = ldg_nc128(wmod + (size_t)ct * 3072 + b * 8), w1 = ldg_nc128(wmod + (size_t)(ct + 256) * 3072 + b * 8);
      const float c0 = __bfloat162float(cvec[ct]), c1 = __bfloat162float(cvec[ct + 256]);
      uint32_t xr[128];
      const __nv_bfloat16* xp = x + (size_t)(rt * 128 + wid * 16) * DM + lane * 8;
#pragma unroll
      for (int i = 0; i < 16; i++) {
        const uint4 u = ldg_nc128(xp + i * DM), v = ldg_nc128(xp + i * DM + 256);
        xr[8 * i] = u.x; xr[8 * i + 1] = u.y; xr[8 * i + 2] = u.z; xr[8 * i + 3] = u.w;
        xr[8 * i + 4] = v.x; xr[8 * i + 5] = v.y; xr[8 * i + 6] = v.z; xr[8 * i + 7] = v.w;
      }
      tag += 1;
      if (ct == 0) sts32(sb + OFF_EPOCH, tag);
      {
        const float s0 = silu_bf(c0), s1 = silu_bf(c1);
        float a[8] = {s0 * blo(w0.x) + s1 * blo(w1.x), s0 * bhi(w0.x) + s1 * bhi(w1.x), s0 * blo(w0.y) + s1 * blo(w1.y), s0 * bhi(w0.y) + s1 * bhi(w1.y),
                      s0 * blo(w0.z) + s1 * blo(w1.z), s0 * bhi(w0.z) + s1 * bhi(w1.z), s0 * blo(w0.w) + s1 * blo(w1.w), s0 * bhi(w0.w) + s1 * bhi(w1.w)};
#pragma unroll
        for (int i = 0; i < 4; i++) { const bool up = lane & 16; const float snd = up ? a[i] : a[i + 4], kp = up ? a[i + 4] : a[i]; a[i] = kp + __shfl_xor_sync(~0u, snd, 16); }
#pragma unroll
        for (int i = 0; i < 2; i++) { const bool up = lane & 8; const float snd = up ? a[i] : a[i + 2], kp = up ? a[i + 2] : a[i]; a[i] = kp + __shfl_xor_sync(~0u, snd, 8); }
        { const bool up = lane & 4; const float snd = up ? a[0] : a[1], kp = up ? a[1] : a[0]; a[0] = kp + __shfl_xor_sync(~0u, snd, 4); }
        a[0] += __shfl_xor_sync(~0u, a[0], 2); a[0] += __shfl_xor_sync(~0u, a[0], 1);
        if ((lane & 3) == 0) sts32(sb + OFF_RED + (wid * 8 + (lane >> 2)) * 4, __float_as_uint(a[0]));
        bar_sync(B_CONS, 256);
        if (ct < 4) {
          float v0 = 0.f, v1 = 0.f;
#pragma unroll
          for (int w = 0; w < 8; w++) { v0 += __uint_as_float(lds32(sb + OFF_RED + (w * 8 + 2 * ct) * 4)); v1 += __uint_as_float(lds32(sb + OFF_RED + (w * 8 + 2 * ct + 1) * 4)); }
          st_ll(&g_modll[b * 4 + ct], pack2(v0, v1), tag);
        }
      }
      TS(0);
      float v[32];
#pragma unroll
      for (int i = 0; i < 16; i++) {
        float s = 0.f, q = 0.f;
#pragma unroll
        for (int j = 0; j < 8; j++) { const float lo = blo(xr[8 * i + j]), hi = bhi(xr[8 * i + j]); s += lo; s += hi; q = fmaf(lo, lo, q); q = fmaf(hi, hi, q); }
        v[2 * i] = s; v[2 * i + 1] = q;
      }
      xreduce<16>(v, lane); xreduce<8>(v, lane); xreduce<4>(v, lane); xreduce<2>(v, lane); xreduce<1>(v, lane);
      float rs, nm;
      {
        const float oth = __shfl_xor_sync(~0u, v[0], 1);
        const float mean = ((lane & 1) ? oth : v[0]) * (1.f / DM), ex = ((lane & 1) ? v[0] : oth) * (1.f / DM);
        const float var = fmaxf(ex - mean * mean, 0.f);
        rs = 1.f / bround(sqrtf(bround(bround(var) + 1e-5f)));
        nm = -bround(mean) * rs;
      }
#pragma unroll
      for (int i = 0; i < 16; i++) {
        const float r = __shfl_sync(~0u, rs, 2 * i), m = __shfl_sync(~0u, nm, 2 * i);
#pragma unroll
        for (int j = 0; j < 8; j++) xr[8 * i + j] = pack2(fmaf(blo(xr[8 * i + j]), r, m), fmaf(bhi(xr[8 * i + j]), r, m));
      }
      pin(xr);
      TS(1);
      {
        const unsigned long long pa = ld_ll(&g_modll[ct]), pc = ld_ll(&g_modll[256 + ct]);
        sts32(sb + OFF_MODSM + ct * 4, get_ll(&g_modll[ct], pa, tag));
        sts32(sb + OFF_MODSM + 1024 + ct * 4, one_plus(get_ll(&g_modll[256 + ct], pc, tag)));
      }
      bar_sync(B_CONS, 256);
      TS(2);
      const uint4 sa0 = lds128(sb + OFF_MODSM + lane * 16), sa1 = lds128(sb + OFF_MODSM + 512 + lane * 16);
      const uint4 ga0 = lds128(sb + OFF_MODSM + 1024 + lane * 16), ga1 = lds128(sb + OFF_MODSM + 1536 + lane * 16);
#pragma unroll
      for (int i = 0; i < 16; i++) {
        const uint32_t row = wid * 16 + i;
        const uint32_t ad = sb + (lane >> 3) * 16384 + row * 128 + (((lane & 7) ^ (i & 7)) << 4);
        const uint32_t h0 = hfma2(xr[8 * i], ga0.x, sa0.x), h1 = hfma2(xr[8 * i + 1], ga0.y, sa0.y), h2 = hfma2(xr[8 * i + 2], ga0.z, sa0.z), h3 = hfma2(xr[8 * i + 3], ga0.w, sa0.w);
        const uint32_t h4 = hfma2(xr[8 * i + 4], ga1.x, sa1.x), h5 = hfma2(xr[8 * i + 5], ga1.y, sa1.y), h6 = hfma2(xr[8 * i + 6], ga1.z, sa1.z), h7 = hfma2(xr[8 * i + 7], ga1.w, sa1.w);
        sts128(ad, h0, h1, h2, h3);
        sts128(ad + 65536, h4, h5, h6, h7);
      }
      fence_async_smem();
      bar_sync(B_WG + cw, 128);
    }
    asm volatile("barrier.cluster.wait.aligned;" ::: "memory");
    TS(3);

    const uint64_t dA0 = make_desc(sb + cw * 8192, 16, 1024);
    const uint64_t dB0 = make_desc(sb, 8192, 1024);
    uint32_t q[32];

    {
      uint32_t held[64];
      float acc[128];
      int s3 = 4, prev = 4;
      uint32_t pf = 0;
#pragma unroll
      for (int pass = 0; pass < 2; pass++) {
#pragma unroll 1
        for (int k = 0; k < 8; k++) {
          mbar_wait(FULL(s3), (pf >> s3) & 1); pf ^= 1u << s3;
          wg_fence();
#pragma unroll
          for (int ks = 0; ks < 4; ks++) wgmma_ss_n256_t1(acc, dA0 + k * 1024 + ks * 2, dB0 + s3 * 2048 + ks * 128, (k | ks) != 0);
          wg_commit();
          if (k > 0) { wg_wait<1>(); release(prev); }
          prev = s3; s3 = s3 == 6 ? 4 : s3 + 1;
        }
        wg_wait<0>(); pin(acc);
        release(prev);
        if (pass == 0) {
#pragma unroll
          for (int j = 0; j < 64; j++) held[j] = pack2(acc[2 * j], acc[2 * j + 1]);
          pin(held);
        }
      }
      release(3);
#pragma unroll
      for (int j = 0; j < 32; j++) q[j] = pack2(acc[2 * j], acc[2 * j + 1]);
#pragma unroll
      for (int kk = 0; kk < 8; kk++) {
        stsm4(frag_addr(0, kk), pack2(acc[64 + 8 * kk], acc[65 + 8 * kk]), pack2(acc[66 + 8 * kk], acc[67 + 8 * kk]), pack2(acc[68 + 8 * kk], acc[69 + 8 * kk]), pack2(acc[70 + 8 * kk], acc[71 + 8 * kk]));
        stsm4(frag_addr(1, kk), held[4 * kk], held[4 * kk + 1], held[4 * kk + 2], held[4 * kk + 3]);
        stsm4(frag_addr(2, kk), held[32 + 4 * kk], held[33 + 4 * kk], held[34 + 4 * kk], held[35 + 4 * kk]);
      }
      pin(q);
    }
    TS(4);

    {
      const float cl2 = 0.08838834764831845f * 1.4426950408889634f;
      const uint64_t dK0 = make_desc(sb + 5 * SLOT, 16, 1024);
      const uint64_t dV0 = make_desc(sb + 3 * SLOT, 16384, 1024);
      float o[64], s[64];
      uint32_t p[32];
      float ms0, ms1, l0, l1, t0, t1;
      auto qk = [&](int st) {
#pragma unroll
        for (int kk = 0; kk < 8; kk++) wgmma_rs_n128_t0(s, q[4 * kk], q[4 * kk + 1], q[4 * kk + 2], q[4 * kk + 3], dK0 + st * 2048 + (kk >> 2) * 1024 + (kk & 3) * 2, kk != 0);
        wg_commit();
      };
      auto pv = [&](int st, int acc) {
#pragma unroll
        for (int kk = 0; kk < 8; kk++) wgmma_rs_n128_t1(o, p[4 * kk], p[4 * kk + 1], p[4 * kk + 2], p[4 * kk + 3], dV0 + st * 2048 + kk * 128, (kk != 0) | acc);
        wg_commit();
      };
      auto rowmax = [&](float& a, float& c) {
        float u[4], w[4];
#pragma unroll
        for (int j = 0; j < 4; j++) { u[j] = fmaxf(s[4 * j], s[4 * j + 1]); w[j] = fmaxf(s[4 * j + 2], s[4 * j + 3]); }
#pragma unroll
        for (int j = 4; j < 16; j++) { u[j & 3] = fmaxf(fmaxf(u[j & 3], s[4 * j]), s[4 * j + 1]); w[j & 3] = fmaxf(fmaxf(w[j & 3], s[4 * j + 2]), s[4 * j + 3]); }
        float x0 = fmaxf(fmaxf(u[0], u[1]), fmaxf(u[2], u[3])), x1 = fmaxf(fmaxf(w[0], w[1]), fmaxf(w[2], w[3]));
        x0 = fmaxf(x0, __shfl_xor_sync(~0u, x0, 1)); x1 = fmaxf(x1, __shfl_xor_sync(~0u, x1, 1));
        x0 = fmaxf(x0, __shfl_xor_sync(~0u, x0, 2)); x1 = fmaxf(x1, __shfl_xor_sync(~0u, x1, 2));
        a = x0 * cl2; c = x1 * cl2;
      };
      auto expsum = [&]() {
#pragma unroll
        for (int j = 0; j < 16; j++) {
          s[4 * j] = ex2(fmaf(s[4 * j], cl2, -ms0)); s[4 * j + 1] = ex2(fmaf(s[4 * j + 1], cl2, -ms0));
          s[4 * j + 2] = ex2(fmaf(s[4 * j + 2], cl2, -ms1)); s[4 * j + 3] = ex2(fmaf(s[4 * j + 3], cl2, -ms1));
          if (j == 0) { t0 = s[0] + s[1]; t1 = s[2] + s[3]; } else { t0 += s[4 * j] + s[4 * j + 1]; t1 += s[4 * j + 2] + s[4 * j + 3]; }
        }
      };
      auto cvtp = [&]() {
#pragma unroll
        for (int j = 0; j < 32; j++) p[j] = pack2(s[2 * j], s[2 * j + 1]);
      };
      auto inv_l = [&](float& i0, float& i1) {
        float a = l0 + __shfl_xor_sync(~0u, l0, 1), c = l1 + __shfl_xor_sync(~0u, l1, 1);
        a += __shfl_xor_sync(~0u, a, 2); c += __shfl_xor_sync(~0u, c, 2);
        i0 = 1.f / a; i1 = 1.f / c;
      };
      if (cw == 0) bar_arrive(B_PP, 256);
      mbar_wait(FULL(5), 1);
      bar_sync(B_PP + cw, 256);
      wg_fence();
      qk(0);
      bar_arrive(B_PP + (cw ^ 1), 256);
      wg_wait<0>(); pin(s);
      release(5);
      rowmax(ms0, ms1);
      expsum();
      cvtp();
      l0 = t0; l1 = t1;
      pin(p);
      TS(5);
#pragma unroll 1
      for (int t = 1; t < 64; t++) {
        const int st = t & 1;
        mbar_wait(FULL(5 + st), ((t >> 1) & 1) ^ 1);
        bar_sync(B_PP + cw, 256);
        wg_fence();
        qk(st);
        mbar_wait(FULL(3 + st), ((t - 1) >> 1) & 1);
        wg_fence();
        pv(st, (t & 15) != 1);
        if (t < 63 || cw == 0) bar_arrive(B_PP + (cw ^ 1), 256);
        wg_wait<1>(); pin(s);
        release(5 + st);
        const bool first = (t & 15) == 0;
        float i0, i1;
        if (first) { inv_l(i0, i1); rowmax(ms0, ms1); l0 = 0.f; l1 = 0.f; }
        expsum();
        wg_wait<0>(); pin(o); pin(p);
        release(3 + st);
        if (first) {
          const int slot = (t >> 4) - 1;
#pragma unroll
          for (int j = 0; j < 16; j++) { p[2 * j] = pack2(o[4 * j] * i0, o[4 * j + 1] * i0); p[2 * j + 1] = pack2(o[4 * j + 2] * i1, o[4 * j + 3] * i1); }
#pragma unroll
          for (int kk = 0; kk < 8; kk++) stsm4(frag_addr(slot, kk), p[4 * kk], p[4 * kk + 1], p[4 * kk + 2], p[4 * kk + 3]);
          fence_async_smem();
        }
        cvtp();
        if (__any_sync(~0u, !(t0 + t1 <= 1.2089258e24f))) {
          const uint32_t* kp = (const uint32_t*)(kc + (size_t)(g * SEQ + (t & 15) * 128 + (lane >> 2)) * DH) + (lane & 3);
#pragma unroll
          for (int j = 0; j < 16; j++) {
            s[4 * j] = 0.f; s[4 * j + 1] = 0.f; s[4 * j + 2] = 0.f; s[4 * j + 3] = 0.f;
#pragma unroll
            for (int kk = 0; kk < 8; kk++)
              mma16816(s[4 * j], s[4 * j + 1], s[4 * j + 2], s[4 * j + 3], q[4 * kk], q[4 * kk + 1], q[4 * kk + 2], q[4 * kk + 3], ldg_nc32(kp + j * 512 + kk * 8), ldg_nc32(kp + j * 512 + kk * 8 + 4));
          }
          float x0, x1;
          rowmax(x0, x1);
          x0 = fmaxf(x0, ms0); x1 = fmaxf(x1, ms1);
          const float a0 = ex2(ms0 - x0), a1 = ex2(ms1 - x1);
          ms0 = x0; ms1 = x1; l0 *= a0; l1 *= a1;
#pragma unroll
          for (int j = 0; j < 16; j++) { o[4 * j] *= a0; o[4 * j + 1] *= a0; o[4 * j + 2] *= a1; o[4 * j + 3] *= a1; }
          expsum();
          cvtp();
        }
        l0 += t0; l1 += t1;
        if ((t & 15) == 15 && t < 63) {
#pragma unroll
          for (int kk = 0; kk < 8; kk++) ldsm4(frag_addr(t >> 4, kk), q[4 * kk], q[4 * kk + 1], q[4 * kk + 2], q[4 * kk + 3]);
        }
        pin(p); pin(o); pin(q);
        asm volatile("" : "+f"(l0), "+f"(l1) :: "memory");
      }
      mbar_wait(FULL(3), 1);
      wg_fence();
      pv(0, 1);
      float i0, i1;
      inv_l(i0, i1);
      wg_wait<0>(); pin(o);
      release(3);
#pragma unroll
      for (int j = 0; j < 16; j++) { q[2 * j] = pack2(o[4 * j] * i0, o[4 * j + 1] * i0); q[2 * j + 1] = pack2(o[4 * j + 2] * i1, o[4 * j + 3] * i1); }
      pin(q);
    }
    TS(10);

    uint4* const part_w = g_part + ((size_t)(rt * 8 + wid) * 8 + g) * 1024 + lane;
    const uint4* const part_r = g_part + (size_t)(rt * 8 + g) * 8 * 1024 + wid * 128 + lane;
    auto store_part = [&](const float (&acc)[128], int pass) {
#pragma unroll
      for (int c = 0; c < 16; c++)
        stg128(part_w + (pass * 16 + c) * 32, pack2(acc[8 * c], acc[8 * c + 1]), pack2(acc[8 * c + 2], acc[8 * c + 3]), pack2(acc[8 * c + 4], acc[8 * c + 5]), pack2(acc[8 * c + 6], acc[8 * c + 7]));
    };
    auto exchange = [&](int phase) {
      fence_gpu();
      bar_sync(B_CONS, 256);
      if (ct == 0) { cnt_signal(&g_cnt[(phase * 16 + rt) * 32]); cnt_wait(&g_cnt[(phase * 16 + rt) * 32], tag * 8); }
      bar_sync(B_CONS, 256);
    };
    auto gather = [&](float (&y)[32]) {
#pragma unroll
      for (int h = 0; h < 2; h++) {
        uint4 u[16];
#pragma unroll
        for (int sg = 0; sg < 4; sg++)
#pragma unroll
          for (int c = 0; c < 4; c++) u[sg * 4 + c] = ldg_cg128(part_r + (h * 4 + sg) * 1024 + c * 32);
#pragma unroll
        for (int sg = 0; sg < 4; sg++)
#pragma unroll
          for (int c = 0; c < 4; c++) {
            const uint4 w = u[sg * 4 + c];
            if (h == 0 && sg == 0) {
              y[8 * c] = blo(w.x); y[8 * c + 1] = bhi(w.x); y[8 * c + 2] = blo(w.y); y[8 * c + 3] = bhi(w.y);
              y[8 * c + 4] = blo(w.z); y[8 * c + 5] = bhi(w.z); y[8 * c + 6] = blo(w.w); y[8 * c + 7] = bhi(w.w);
            } else {
              y[8 * c] += blo(w.x); y[8 * c + 1] += bhi(w.x); y[8 * c + 2] += blo(w.y); y[8 * c + 3] += bhi(w.y);
              y[8 * c + 4] += blo(w.z); y[8 * c + 5] += bhi(w.z); y[8 * c + 6] += blo(w.w); y[8 * c + 7] += bhi(w.w);
            }
          }
      }
    };
    auto write_rows = [&](const uint32_t (&w)[16], __nv_bfloat16* dst) {
#pragma unroll
      for (int c = 0; c < 4; c++) stsm4(sb + (lane & 15) * STG_PITCH + (wid * 64 + c * 16 + (lane >> 4) * 8) * 2, w[4 * c], w[4 * c + 1], w[4 * c + 2], w[4 * c + 3]);
      fence_async_smem();
      bar_sync(B_CONS, 256);
      if (ct < 16) {
        bulk_store(dst + (size_t)(rt * 128 + g * 16 + ct) * DM, sb + ct * STG_PITCH, 1024);
        asm volatile("cp.async.bulk.commit_group;" ::: "memory");
      }
    };
    const int mcol = wid * 32 + (lane & 3);

    {
      float acc[128];
#pragma unroll 1
      for (int pass = 0; pass < 2; pass++) {
        int prev = 0;
#pragma unroll 1
        for (int k = 0; k < 6; k++) {
          const int s = (0x3465 >> ((k & 3) * 4)) & 7;
          mbar_wait(FULL(s), ((k >> 2) & 1) ^ (s >= 5));
          wg_fence();
#pragma unroll
          for (int ks = 0; ks < 4; ks++) wgmma_ss_n256_t1(acc, dA0 + k * 1024 + ks * 2, dB0 + s * 2048 + ks * 128, (k | ks) != 0);
          wg_commit();
          if (k > 0) { wg_wait<1>(); release(prev); }
          prev = s;
        }
        mbar_wait(FULL(4), 1);
        wg_fence();
#pragma unroll
        for (int ks = 0; ks < 4; ks++) wgmma_rs_n256_t1(acc, q[4 * ks], q[4 * ks + 1], q[4 * ks + 2], q[4 * ks + 3], dB0 + 4 * 2048 + ks * 128, 1);
        wg_commit();
        wg_wait<1>(); release(6);
        mbar_wait(FULL(3), 1);
        wg_fence();
#pragma unroll
        for (int ks = 0; ks < 4; ks++) wgmma_rs_n256_t1(acc, q[16 + 4 * ks], q[17 + 4 * ks], q[18 + 4 * ks], q[19 + 4 * ks], dB0 + 3 * 2048 + ks * 128, 1);
        wg_commit();
        wg_wait<1>(); release(4);
        wg_wait<0>(); pin(acc); pin(q);
        if (pass == 0) release(3);
        store_part(acc, pass);
      }
    }
    TS(11);

    uint32_t x1[16];
    {
      uint32_t ga[8], cb[8], sbv[8];
      {
        unsigned long long pg[8], ps[8], pc[8];
#pragma unroll
        for (int j = 0; j < 8; j++) { pg[j] = ld_ll(&g_modll[512 + mcol + 4 * j]); ps[j] = ld_ll(&g_modll[768 + mcol + 4 * j]); pc[j] = ld_ll(&g_modll[1024 + mcol + 4 * j]); }
        const uint32_t* xp = (const uint32_t*)(x + (size_t)(rt * 128 + g * 16 + (lane >> 2)) * DM) + mcol;
#pragma unroll
        for (int j = 0; j < 8; j++) { x1[2 * j] = ldg_nc32(xp + 4 * j); x1[2 * j + 1] = ldg_nc32(xp + 8 * (DM / 2) + 4 * j); }
#pragma unroll
        for (int j = 0; j < 8; j++) {
          ga[j] = get_ll(&g_modll[512 + mcol + 4 * j], pg[j], tag); sbv[j] = get_ll(&g_modll[768 + mcol + 4 * j], ps[j], tag);
          cb[j] = one_plus(get_ll(&g_modll[1024 + mcol + 4 * j], pc[j], tag));
        }
      }
      exchange(0);
      TS(12);
      float y[32];
      gather(y);
      float s0 = 0.f, q0 = 0.f, s1 = 0.f, q1 = 0.f;
#pragma unroll
      for (int j = 0; j < 8; j++) {
        x1[2 * j] = pack2(fmaf(blo(ga[j]), y[4 * j], blo(x1[2 * j])), fmaf(bhi(ga[j]), y[4 * j + 1], bhi(x1[2 * j])));
        x1[2 * j + 1] = pack2(fmaf(blo(ga[j]), y[4 * j + 2], blo(x1[2 * j + 1])), fmaf(bhi(ga[j]), y[4 * j + 3], bhi(x1[2 * j + 1])));
        y[4 * j] = blo(x1[2 * j]); y[4 * j + 1] = bhi(x1[2 * j]); y[4 * j + 2] = blo(x1[2 * j + 1]); y[4 * j + 3] = bhi(x1[2 * j + 1]);
        s0 += y[4 * j] + y[4 * j + 1]; q0 = fmaf(y[4 * j], y[4 * j], q0); q0 = fmaf(y[4 * j + 1], y[4 * j + 1], q0);
        s1 += y[4 * j + 2] + y[4 * j + 3]; q1 = fmaf(y[4 * j + 2], y[4 * j + 2], q1); q1 = fmaf(y[4 * j + 3], y[4 * j + 3], q1);
      }
#pragma unroll
      for (int o = 1; o < 4; o <<= 1) { s0 += __shfl_xor_sync(~0u, s0, o); q0 += __shfl_xor_sync(~0u, q0, o); s1 += __shfl_xor_sync(~0u, s1, o); q1 += __shfl_xor_sync(~0u, q1, o); }
      if ((lane & 3) == 0) sts128(sb + OFF_MODSM + (wid * 8 + (lane >> 2)) * 16, __float_as_uint(s0), __float_as_uint(q0), __float_as_uint(s1), __float_as_uint(q1));
      bar_sync(B_CONS, 256);
      s0 = q0 = s1 = q1 = 0.f;
#pragma unroll
      for (int w = 0; w < 8; w++) { const uint4 u = lds128(sb + OFF_MODSM + (w * 8 + (lane >> 2)) * 16); s0 += __uint_as_float(u.x); q0 += __uint_as_float(u.y); s1 += __uint_as_float(u.z); q1 += __uint_as_float(u.w); }
      const float m0 = s0 * (1.f / DM), m1 = s1 * (1.f / DM);
      const float r0 = 1.f / bround(sqrtf(bround(bround(fmaxf(q0 * (1.f / DM) - m0 * m0, 0.f)) + 1e-5f)));
      const float r1 = 1.f / bround(sqrtf(bround(bround(fmaxf(q1 * (1.f / DM) - m1 * m1, 0.f)) + 1e-5f)));
      const float n0 = -bround(m0) * r0, n1 = -bround(m1) * r1;
      uint32_t hw[16];
#pragma unroll
      for (int j = 0; j < 8; j++) {
        hw[2 * j] = hfma2(pack2(fmaf(y[4 * j], r0, n0), fmaf(y[4 * j + 1], r0, n0)), cb[j], sbv[j]);
        hw[2 * j + 1] = hfma2(pack2(fmaf(y[4 * j + 2], r1, n1), fmaf(y[4 * j + 3], r1, n1)), cb[j], sbv[j]);
      }
      write_rows(hw, g_h2);
      if (wid == 0) {
        asm volatile("cp.async.bulk.wait_group 0;" ::: "memory");
        fence_async_all();
        fence_gpu();
        __syncwarp();
        if (lane == 0) cnt_signal(&g_cnt[(16 + rt) * 32]);
      }
      pin(x1);
    }
    TS(13);

    {
      uint32_t act[56];
      int s3 = 5, prev = 5;
      uint32_t pf = 0x60;
      auto swiglu = [&](float gt0, float gt1, float up0, float up1) {
        const float h0 = 0.5f * gt0, h1 = 0.5f * gt1;
        return pack2(fmaf(h0, tanh_fast(h0), h0) * up0, fmaf(h1, tanh_fast(h1), h1) * up1);
      };
      {
        float acc[128];
#pragma unroll 1
        for (int k = 0; k < 8; k++) {
          if ((k & 1) == 0) mbar_wait(FULL(k >> 1), k == 6 ? 0 : 0);
          mbar_wait(FULL(s3), (pf >> s3) & 1); pf ^= 1u << s3;
          wg_fence();
#pragma unroll
          for (int ks = 0; ks < 4; ks++) wgmma_ss_n256_t1(acc, dA0 + k * 1024 + ks * 2, dB0 + s3 * 2048 + ks * 128, (k | ks) != 0);
          wg_commit();
          if (k > 0) { wg_wait<1>(); release(prev); }
          prev = s3; s3 = s3 == 6 ? 4 : s3 + 1;
          if (k == 0) TS(14);
        }
        wg_wait<0>(); pin(acc);
        release(prev);
#pragma unroll
        for (int j = 0; j < 32; j++) act[j] = swiglu(acc[2 * j], acc[2 * j + 1], acc[64 + 2 * j], acc[65 + 2 * j]);
      }
      {
        float ag[48], au[48];
#pragma unroll 1
        for (int k = 0; k < 8; k++) {
          mbar_wait(FULL(s3), (pf >> s3) & 1); pf ^= 1u << s3;
          wg_fence();
#pragma unroll
          for (int ks = 0; ks < 4; ks++) {
            wgmma_ss_n96_t1(ag, dA0 + k * 1024 + ks * 2, dB0 + s3 * 2048 + ks * 128, (k | ks) != 0);
            wgmma_ss_n96_t1(au, dA0 + k * 1024 + ks * 2, dB0 + s3 * 2048 + 1024 + ks * 128, (k | ks) != 0);
          }
          wg_commit();
          if (k > 0) { wg_wait<1>(); release(prev); }
          prev = s3; s3 = s3 == 6 ? 4 : s3 + 1;
        }
        wg_wait<0>(); pin(ag); pin(au);
        release(prev);
#pragma unroll
        for (int j = 0; j < 24; j++) act[32 + j] = swiglu(ag[2 * j], ag[2 * j + 1], au[2 * j], au[2 * j + 1]);
      }
      pin(act);
      TS(15);
      float acc[128];
#pragma unroll 1
      for (int pass = 0; pass < 2; pass++) {
#pragma unroll
        for (int k = 0; k < 4; k++) {
          mbar_wait(FULL(s3), (pf >> s3) & 1); pf ^= 1u << s3;
          wg_fence();
#pragma unroll
          for (int ks = 0; ks < (k < 3 ? 4 : 2); ks++) wgmma_rs_n256_t1(acc, act[16 * k + 4 * ks], act[16 * k + 4 * ks + 1], act[16 * k + 4 * ks + 2], act[16 * k + 4 * ks + 3], dB0 + s3 * 2048 + ks * 128, (k | ks) != 0);
          wg_commit();
          if (k > 0) { wg_wait<1>(); if (pass == 0 || k == 1) release(prev); }
          prev = s3; s3 = s3 == 6 ? 4 : s3 + 1;
        }
        wg_wait<0>(); pin(acc); pin(act);
        if (pass == 0) release(prev);
        store_part(acc, pass);
      }
    }
    asm volatile("barrier.cluster.arrive.relaxed.aligned;" ::: "memory");
    TS(16);

    {
      uint32_t gb[8];
      {
        unsigned long long pg[8];
#pragma unroll
        for (int j = 0; j < 8; j++) pg[j] = ld_ll(&g_modll[1280 + mcol + 4 * j]);
#pragma unroll
        for (int j = 0; j < 8; j++) gb[j] = get_ll(&g_modll[1280 + mcol + 4 * j], pg[j], tag);
      }
      exchange(2);
      TS(17);
      if (b == 0 && ct == 0) g_epoch = tag;
      float y[32];
      gather(y);
      uint32_t ow[16];
#pragma unroll
      for (int j = 0; j < 8; j++) {
        ow[2 * j] = pack2(fmaf(blo(gb[j]), y[4 * j], blo(x1[2 * j])), fmaf(bhi(gb[j]), y[4 * j + 1], bhi(x1[2 * j])));
        ow[2 * j + 1] = pack2(fmaf(blo(gb[j]), y[4 * j + 2], blo(x1[2 * j + 1])), fmaf(bhi(gb[j]), y[4 * j + 3], bhi(x1[2 * j + 1])));
      }
      write_rows(ow, out);
      if (wid == 0) asm volatile("cp.async.bulk.wait_group.read 0;" ::: "memory");
    }
    TS(18);
    asm volatile("barrier.cluster.wait.aligned;" ::: "memory");
  }
}

typedef CUresult (*EncodeFn)(CUtensorMap*, CUtensorMapDataType, cuuint32_t, void*, const cuuint64_t*, const cuuint64_t*, const cuuint32_t*, const cuuint32_t*,
                             CUtensorMapInterleave, CUtensorMapSwizzle, CUtensorMapL2promotion, CUtensorMapFloatOOBfill);

void make_map(EncodeFn fn, CUtensorMap* m, const void* p, uint64_t rows, uint64_t cols, uint32_t box_rows) {
  cuuint64_t dims[2] = {cols, rows};
  cuuint64_t strides[1] = {cols * 2};
  cuuint32_t box[2] = {64, box_rows};
  cuuint32_t es[2] = {1, 1};
  fn(m, CU_TENSOR_MAP_DATA_TYPE_BFLOAT16, 2, const_cast<void*>(p), dims, strides, box, es, CU_TENSOR_MAP_INTERLEAVE_NONE, CU_TENSOR_MAP_SWIZZLE_128B,
     CU_TENSOR_MAP_L2_PROMOTION_L2_128B, CU_TENSOR_MAP_FLOAT_OOB_FILL_NONE);
}

}

extern "C" void kernel_launch(void* const* d_in, const int* in_sizes, int n_in, void* d_out, int out_size) {
  (void)in_sizes; (void)n_in; (void)out_size;
  typedef const __nv_bfloat16* P;
  P x = (P)d_in[0], k = (P)d_in[1], v = (P)d_in[2], wq = (P)d_in[3], wo = (P)d_in[4];
  P wg = (P)d_in[6], wu = (P)d_in[7], wd = (P)d_in[8], c = (P)d_in[9], wmod = (P)d_in[10];
  static EncodeFn fn = nullptr;
  static void* h2p = nullptr;
  if (!fn) {
    void* p = nullptr;
    cudaDriverEntryPointQueryResult qr;
    cudaGetDriverEntryPoint("cuTensorMapEncodeTiled", &p, cudaEnableDefault, &qr);
    fn = (EncodeFn)p;
    cudaGetSymbolAddress(&h2p, g_h2);
    cudaFuncSetAttribute(fused_kernel, cudaFuncAttributeMaxDynamicSharedMemorySize, SMEM_BYTES);
  }
  Maps mp;
  make_map(fn, &mp.wq, wq, 512, 4096, 64);
  make_map(fn, &mp.k, k, 8 * SEQ, DH, 128);
  make_map(fn, &mp.v, v, 8 * SEQ, DH, 128);
  make_map(fn, &mp.wo, wo, 4096, DM, 64);
  make_map(fn, &mp.wg, wg, DM, FF, 64);
  make_map(fn, &mp.wu, wu, DM, FF, 64);
  make_map(fn, &mp.wd, wd, FF, DM, 64);
  make_map(fn, &mp.h2, h2p, SEQ, DM, 128);
  fused_kernel<<<128, 384, SMEM_BYTES>>>(mp, x, k, wo, wg, wu, wd, c, wmod, (__nv_bfloat16*)d_out);
}
```

```cpp
#include <cuda_runtime.h>
#include <cuda_bf16.h>
#include <cuda.h>
#include <stdint.h>

namespace {

constexpr int SEQ = 2048, DM = 512, DH = 128, FF = 1792, FS = 224;
constexpr int SLOT = 32768;
constexpr int OFF_BAR = 7 * SLOT;
constexpr int OFF_MODSM = OFF_BAR + 128;
constexpr int OFF_RED = OFF_MODSM + 2048;
constexpr int OFF_RED2 = OFF_RED + 256;
constexpr int OFF_EPOCH = OFF_RED2 + 192;
constexpr int SMEM_BYTES = 232448;
static_assert(OFF_EPOCH + 16 <= SMEM_BYTES, "smem");
constexpr int STG_PITCH = 1040;

constexpr int CONS_REGS = 232, PROD_REGS = 40;
#define EXP_SPLIT 11

__device__ uint4 g_part[16 * 8 * 8 * 1024];
__device__ __nv_bfloat16 g_h2[SEQ * DM];
__device__ unsigned long long g_modll[1536];
__device__ unsigned int g_cnt[3 * 16 * 32];
__device__ unsigned int g_epoch;

struct Maps { CUtensorMap wq, k, v, wo, wg, wu, wd, h2; };

__device__ __forceinline__ uint32_t smem_u32(const void* p) { return (uint32_t)__cvta_generic_to_shared(p); }
__device__ __forceinline__ void mbar_init(uint32_t bar, uint32_t cnt) { asm volatile("mbarrier.init.shared::cta.b64 [%0], %1;" :: "r"(bar), "r"(cnt) : "memory"); }
__device__ __forceinline__ void mbar_expect_tx(uint32_t bar, uint32_t bytes) { asm volatile("mbarrier.arrive.expect_tx.shared::cta.b64 _, [%0], %1;" :: "r"(bar), "r"(bytes) : "memory"); }
__device__ __forceinline__ void mbar_arrive_cluster(uint32_t bar, uint32_t cta) {
  asm volatile("{\n.reg .b32 ra;\nmapa.shared::cluster.u32 ra, %0, %1;\nmbarrier.arrive.shared::cluster.b64 _, [ra];\n}" :: "r"(bar), "r"(cta) : "memory");
}
__device__ __forceinline__ void mbar_wait(uint32_t bar, uint32_t par) {
  asm volatile(
    "{\n.reg .pred p;\n.reg .u32 n;\n"
    "mbarrier.try_wait.parity.shared::cta.b64 p, [%0], %1;\n"
    "@p bra W_DONE;\n"
    "mov.u32 n, 0;\n"
    "W_LOOP:\n"
    "mbarrier.try_wait.parity.shared::cta.b64 p, [%0], %1;\n"
    "@p bra W_DONE;\n"
    "add.u32 n, n, 1;\n"
    "setp.lt.u32 p, n, 0x1000000;\n"
    "@p bra W_LOOP;\n"
    "trap;\n"
    "W_DONE:\n}" :: "r"(bar), "r"(par) : "memory");
}
__device__ __forceinline__ void tma_load(uint32_t dst, const CUtensorMap* m, uint32_t bar, int c0, int c1) {
  asm volatile("cp.async.bulk.tensor.2d.shared::cluster.global.mbarrier::complete_tx::bytes [%0], [%1, {%3, %4}], [%2];" :: "r"(dst), "l"(m), "r"(bar), "r"(c0), "r"(c1) : "memory");
}
__device__ __forceinline__ void tma_load_mc(uint32_t dst, const CUtensorMap* m, uint32_t bar, int c0, int c1) {
  asm volatile("cp.async.bulk.tensor.2d.shared::cluster.global.mbarrier::complete_tx::bytes.multicast::cluster [%0], [%1, {%3, %4}], [%2], %5;" :: "r"(dst), "l"(m), "r"(bar), "r"(c0), "r"(c1), "h"((uint16_t)3) : "memory");
}
__device__ __forceinline__ void tma_prefetch(const CUtensorMap* m, int c0, int c1) {
  asm volatile("cp.async.bulk.prefetch.tensor.2d.L2.global [%0, {%1, %2}];" :: "l"(m), "r"(c0), "r"(c1) : "memory");
}
__device__ __forceinline__ void bulk_prefetch(const void* p, uint32_t bytes) {
  asm volatile("cp.async.bulk.prefetch.L2.global [%0], %1;" :: "l"(p), "r"(bytes) : "memory");
}
__device__ __forceinline__ void bulk_store(void* dst, uint32_t src, uint32_t bytes) {
  asm volatile("cp.async.bulk.global.shared::cta.bulk_group [%0], [%1], %2;" :: "l"(dst), "r"(src), "r"(bytes) : "memory");
}
__device__ __forceinline__ void desc_prefetch(const CUtensorMap* m) { asm volatile("prefetch.tensormap [%0];" :: "l"(m) : "memory"); }
__device__ __forceinline__ void fence_async_smem() { asm volatile("fence.proxy.async.shared::cta;" ::: "memory"); }
__device__ __forceinline__ void fence_async_all() { asm volatile("fence.proxy.async;" ::: "memory"); }
__device__ __forceinline__ void fence_gpu() { asm volatile("fence.acq_rel.gpu;" ::: "memory"); }
__device__ __forceinline__ void bar_sync(int id, int n) { asm volatile("bar.sync %0, %1;" :: "r"(id), "r"(n) : "memory"); }
__device__ __forceinline__ void bar_arrive(int id, int n) { asm volatile("bar.arrive %0, %1;" :: "r"(id), "r"(n) : "memory"); }
__device__ __forceinline__ void wg_fence() { asm volatile("wgmma.fence.sync.aligned;" ::: "memory"); }
__device__ __forceinline__ void wg_commit() { asm volatile("wgmma.commit_group.sync.aligned;" ::: "memory"); }
template <int N> __device__ __forceinline__ void wg_wait() { asm volatile("wgmma.wait_group.sync.aligned %0;" :: "n"(N) : "memory"); }
template <int N> __device__ __forceinline__ void pin(float (&r)[N]) {
#pragma unroll
  for (int i = 0; i < N; i++) asm volatile("" : "+f"(r[i]) :: "memory");
}
template <int N> __device__ __forceinline__ void pin(uint32_t (&r)[N]) {
#pragma unroll
  for (int i = 0; i < N; i++) asm volatile("" : "+r"(r[i]) :: "memory");
}
__device__ __forceinline__ uint64_t make_desc(uint32_t addr, uint32_t lbo, uint32_t sbo) {
  return (uint64_t)((addr & 0x3FFFF) >> 4) | ((uint64_t)(lbo >> 4) << 16) | ((uint64_t)(sbo >> 4) << 32) | (1ull << 62);
}
__device__ __forceinline__ float ex2(float x) { float y; asm("ex2.approx.ftz.f32 %0, %1;" : "=f"(y) : "f"(x)); return y; }
__device__ __forceinline__ float tanh_fast(float x) { float y; asm("tanh.approx.f32 %0, %1;" : "=f"(y) : "f"(x)); return y; }
__device__ __forceinline__ uint32_t pack2(float lo, float hi) { uint32_t r; asm("cvt.rn.bf16x2.f32 %0, %1, %2;" : "=r"(r) : "f"(hi), "f"(lo)); return r; }
__device__ __forceinline__ float blo(uint32_t w) { return __uint_as_float(w << 16); }
__device__ __forceinline__ float bhi(uint32_t w) { return __uint_as_float(w & 0xffff0000u); }
__device__ __forceinline__ float bround(float x) { return blo(pack2(x, 0.f)); }
__device__ __forceinline__ uint32_t hfma2(uint32_t a, uint32_t b, uint32_t c) { uint32_t r; asm("fma.rn.bf16x2 %0, %1, %2, %3;" : "=r"(r) : "r"(a), "r"(b), "r"(c)); return r; }
__device__ __forceinline__ uint32_t one_plus(uint32_t w) { return pack2(1.f + blo(w), 1.f + bhi(w)); }
__device__ __forceinline__ void ldsm4(uint32_t addr, uint32_t& a, uint32_t& b, uint32_t& c, uint32_t& d) {
  asm volatile("ldmatrix.sync.aligned.m8n8.x4.shared.b16 {%0,%1,%2,%3}, [%4];" : "=r"(a), "=r"(b), "=r"(c), "=r"(d) : "r"(addr) : "memory");
}
__device__ __forceinline__ void stsm4(uint32_t addr, uint32_t a, uint32_t b, uint32_t c, uint32_t d) {
  asm volatile("stmatrix.sync.aligned.m8n8.x4.shared.b16 [%0], {%1,%2,%3,%4};" :: "r"(addr), "r"(a), "r"(b), "r"(c), "r"(d) : "memory");
}
__device__ __forceinline__ void sts128(uint32_t addr, uint32_t a, uint32_t b, uint32_t c, uint32_t d) {
  asm volatile("st.shared.v4.b32 [%0], {%1,%2,%3,%4};" :: "r"(addr), "r"(a), "r"(b), "r"(c), "r"(d) : "memory");
}
__device__ __forceinline__ uint4 lds128(uint32_t addr) {
  uint4 v; asm volatile("ld.shared.v4.b32 {%0,%1,%2,%3}, [%4];" : "=r"(v.x), "=r"(v.y), "=r"(v.z), "=r"(v.w) : "r"(addr) : "memory"); return v;
}
__device__ __forceinline__ void sts32(uint32_t addr, uint32_t v) { asm volatile("st.shared.b32 [%0], %1;" :: "r"(addr), "r"(v) : "memory"); }
__device__ __forceinline__ uint32_t lds32(uint32_t addr) { uint32_t v; asm volatile("ld.shared.b32 %0, [%1];" : "=r"(v) : "r"(addr) : "memory"); return v; }
__device__ __forceinline__ uint4 ldg_nc128(const void* p) {
  uint4 v; asm volatile("ld.global.nc.v4.b32 {%0,%1,%2,%3}, [%4];" : "=r"(v.x), "=r"(v.y), "=r"(v.z), "=r"(v.w) : "l"(p)); return v;
}
__device__ __forceinline__ uint4 ldg_cg128(const void* p) {
  uint4 v; asm volatile("ld.global.cg.v4.b32 {%0,%1,%2,%3}, [%4];" : "=r"(v.x), "=r"(v.y), "=r"(v.z), "=r"(v.w) : "l"(p) : "memory"); return v;
}
__device__ __forceinline__ uint32_t ldg_nc32(const void* p) { uint32_t v; asm volatile("ld.global.nc.b32 %0, [%1];" : "=r"(v) : "l"(p)); return v; }
__device__ __forceinline__ void stg128(void* p, uint32_t a, uint32_t b, uint32_t c, uint32_t d) {
  asm volatile("st.global.v4.b32 [%0], {%1,%2,%3,%4};" :: "l"(p), "r"(a), "r"(b), "r"(c), "r"(d) : "memory");
}
__device__ __forceinline__ unsigned long long ld_ll(const unsigned long long* p) {
  unsigned long long v; asm volatile("ld.relaxed.gpu.global.b64 %0, [%1];" : "=l"(v) : "l"(p) : "memory"); return v;
}
__device__ __forceinline__ void st_ll(unsigned long long* p, uint32_t val, uint32_t tag) {
  asm volatile("st.relaxed.gpu.global.b64 [%0], %1;" :: "l"(p), "l"(((unsigned long long)tag << 32) | val) : "memory");
}
__device__ __forceinline__ uint32_t get_ll(const unsigned long long* p, unsigned long long v, uint32_t tag) {
  uint32_t r;
  asm volatile(
    "{\n.reg .pred p;\n.reg .u32 n, t;\n.reg .b64 v;\n"
    "mov.b64 {%0, t}, %2;\n"
    "setp.eq.u32 p, t, %3;\n"
    "@p bra L_DONE;\n"
    "mov.u32 n, 0;\n"
    "L_LOOP:\n"
    "ld.relaxed.gpu.global.b64 v, [%1];\n"
    "mov.b64 {%0, t}, v;\n"
    "setp.eq.u32 p, t, %3;\n"
    "@p bra L_DONE;\n"
    "add.u32 n, n, 1;\n"
    "setp.lt.u32 p, n, 0x1000000;\n"
    "@p bra L_LOOP;\n"
    "trap;\n"
    "L_DONE:\n}" : "=&r"(r) : "l"(p), "l"(v), "r"(tag) : "memory");
  return r;
}
__device__ __forceinline__ void cnt_signal(unsigned int* c) { asm volatile("red.release.gpu.global.add.u32 [%0], 1;" :: "l"(c) : "memory"); }
__device__ __forceinline__ void cnt_wait(const unsigned int* c, uint32_t target) {
  asm volatile(
    "{\n.reg .pred p;\n.reg .u32 n, x;\n"
    "mov.u32 n, 0;\n"
    "C_LOOP:\n"
    "ld.acquire.gpu.global.u32 x, [%0];\n"
    "sub.u32 x, x, %1;\n"
    "setp.ge.s32 p, x, 0;\n"
    "@p bra C_DONE;\n"
    "add.u32 n, n, 1;\n"
    "setp.lt.u32 p, n, 0x1000000;\n"
    "@p bra C_LOOP;\n"
    "trap;\n"
    "C_DONE:\n}" :: "l"(c), "r"(target) : "memory");
}
__device__ __forceinline__ float silu_bf(float x) { return bround(x / (1.f + __expf(-x))); }
__device__ __forceinline__ void mma16816(float& c0, float& c1, float& c2, float& c3, uint32_t a0, uint32_t a1, uint32_t a2, uint32_t a3, uint32_t b0, uint32_t b1) {
  asm("mma.sync.aligned.m16n8k16.row.col.f32.bf16.bf16.f32 {%0,%1,%2,%3}, {%4,%5,%6,%7}, {%8,%9}, {%0,%1,%2,%3};"
      : "+f"(c0), "+f"(c1), "+f"(c2), "+f"(c3) : "r"(a0), "r"(a1), "r"(a2), "r"(a3), "r"(b0), "r"(b1));
}

template <int O, int N> __device__ __forceinline__ void xreduce(float (&v)[N], int lane) {
  const bool up = lane & O;
#pragma unroll
  for (int i = 0; i < O; i++) { const float snd = up ? v[i] : v[i + O], kp = up ? v[i + O] : v[i]; v[i] = kp + __shfl_xor_sync(~0u, snd, O); }
}

template <int N> struct IC { __device__ constexpr operator int() const { return N; } };

__device__ __forceinline__ void wgmma_rs_n128_t0(float (&d)[64], uint32_t a0, uint32_t a1, uint32_t a2, uint32_t a3, uint64_t db, int scale_d) {
  asm volatile(
    "{\n.reg .pred p;\nsetp.ne.b32 p, %69, 0;\n"
    "wgmma.mma_async.sync.aligned.m64n128k16.f32.bf16.bf16 {"
    "%0, %1, %2, %3, %4, %5, %6, %7, %8, %9, %10, %11, %12, %13, %14, %15, "
    "%16, %17, %18, %19, %20, %21, %22, %23, %24, %25, %26, %27, %28, %29, %30, %31, "
    "%32, %33, %34, %35, %36, %37, %38, %39, %40, %41, %42, %43, %44, %45, %46, %47, "
    "%48, %49, %50, %51, %52, %53, %54, %55, %56, %57, %58, %59, %60, %61, %62, %63"
    "}, {%64, %65, %66, %67}, %68, p, 1, 1, 0;\n}\n"
    : "+f"(d[0]), "+f"(d[1]), "+f"(d[2]), "+f"(d[3]), "+f"(d[4]), "+f"(d[5]), "+f"(d[6]), "+f"(d[7]),
      "+f"(d[8]), "+f"(d[9]), "+f"(d[10]), "+f"(d[11]), "+f"(d[12]), "+f"(d[13]), "+f"(d[14]), "+f"(d[15]),
      "+f"(d[16]), "+f"(d[17]), "+f"(d[18]), "+f"(d[19]), "+f"(d[20]), "+f"(d[21]), "+f"(d[22]), "+f"(d[23]),
      "+f"(d[24]), "+f"(d[25]), "+f"(d[26]), "+f"(d[27]), "+f"(d[28]), "+f"(d[29]), "+f"(d[30]), "+f"(d[31]),
      "+f"(d[32]), "+f"(d[33]), "+f"(d[34]), "+f"(d[35]), "+f"(d[36]), "+f"(d[37]), "+f"(d[38]), "+f"(d[39]),
      "+f"(d[40]), "+f"(d[41]), "+f"(d[42]), "+f"(d[43]), "+f"(d[44]), "+f"(d[45]), "+f"(d[46]), "+f"(d[47]),
      "+f"(d[48]), "+f"(d[49]), "+f"(d[50]), "+f"(d[51]), "+f"(d[52]), "+f"(d[53]), "+f"(d[54]), "+f"(d[55]),
      "+f"(d[56]), "+f"(d[57]), "+f"(d[58]), "+f"(d[59]), "+f"(d[60]), "+f"(d[61]), "+f"(d[62]), "+f"(d[63])
    : "r"(a0), "r"(a1), "r"(a2), "r"(a3), "l"(db), "r"(scale_d));
}
__device__ __forceinline__ void wgmma_rs_n128_t1(float (&d)[64], uint32_t a0, uint32_t a1, uint32_t a2, uint32_t a3, uint64_t db, int scale_d) {
  asm volatile(
    "{\n.reg .pred p;\nsetp.ne.b32 p, %69, 0;\n"
    "wgmma.mma_async.sync.aligned.m64n128k16.f32.bf16.bf16 {"
    "%0, %1, %2, %3, %4, %5, %6, %7, %8, %9, %10, %11, %12, %13, %14, %15, "
    "%16, %17, %18, %19, %20, %21, %22, %23, %24, %25, %26, %27, %28, %29, %30, %31, "
    "%32, %33, %34, %35, %36, %37, %38, %39, %40, %41, %42, %43, %44, %45, %46, %47, "
    "%48, %49, %50, %51, %52, %53, %54, %55, %56, %57, %58, %59, %60, %61, %62, %63"
    "}, {%64, %65, %66, %67}, %68, p, 1, 1, 1;\n}\n"
    : "+f"(d[0]), "+f"(d[1]), "+f"(d[2]), "+f"(d[3]), "+f"(d[4]), "+f"(d[5]), "+f"(d[6]), "+f"(d[7]),
      "+f"(d[8]), "+f"(d[9]), "+f"(d[10]), "+f"(d[11]), "+f"(d[12]), "+f"(d[13]), "+f"(d[14]), "+f"(d[15]),
      "+f"(d[16]), "+f"(d[17]), "+f"(d[18]), "+f"(d[19]), "+f"(d[20]), "+f"(d[21]), "+f"(d[22]), "+f"(d[23]),
      "+f"(d[24]), "+f"(d[25]), "+f"(d[26]), "+f"(d[27]), "+f"(d[28]), "+f"(d[29]), "+f"(d[30]), "+f"(d[31]),
      "+f"(d[32]), "+f"(d[33]), "+f"(d[34]), "+f"(d[35]), "+f"(d[36]), "+f"(d[37]), "+f"(d[38]), "+f"(d[39]),
      "+f"(d[40]), "+f"(d[41]), "+f"(d[42]), "+f"(d[43]), "+f"(d[44]), "+f"(d[45]), "+f"(d[46]), "+f"(d[47]),
      "+f"(d[48]), "+f"(d[49]), "+f"(d[50]), "+f"(d[51]), "+f"(d[52]), "+f"(d[53]), "+f"(d[54]), "+f"(d[55]),
      "+f"(d[56]), "+f"(d[57]), "+f"(d[58]), "+f"(d[59]), "+f"(d[60]), "+f"(d[61]), "+f"(d[62]), "+f"(d[63])
    : "r"(a0), "r"(a1), "r"(a2), "r"(a3), "l"(db), "r"(scale_d));
}
__device__ __forceinline__ void wgmma_ss_n256_t1(float (&d)[128], uint64_t da, uint64_t db, int scale_d) {
  asm volatile(
    "{\n.reg .pred p;\nsetp.ne.b32 p, %130, 0;\n"
    "wgmma.mma_async.sync.aligned.m64n256k16.f32.bf16.bf16 {"
    "%0, %1, %2, %3, %4, %5, %6, %7, %8, %9, %10, %11, %12, %13, %14, %15, "
    "%16, %17, %18, %19, %20, %21, %22, %23, %24, %25, %26, %27, %28, %29, %30, %31, "
    "%32, %33, %34, %35, %36, %37, %38, %39, %40, %41, %42, %43, %44, %45, %46, %47, "
    "%48, %49, %50, %51, %52, %53, %54, %55, %56, %57, %58, %59, %60, %61, %62, %63, "
    "%64, %65, %66, %67, %68, %69, %70, %71, %72, %73, %74, %75, %76, %77, %78, %79, "
    "%80, %81, %82, %83, %84, %85, %86, %87, %88, %89, %90, %91, %92, %93, %94, %95, "
    "%96, %97, %98, %99, %100, %101, %102, %103, %104, %105, %106, %107, %108, %109, %110, %111, "
    "%112, %113, %114, %115, %116, %117, %118, %119, %120, %121, %122, %123, %124, %125, %126, %127"
    "}, %128, %129, p, 1, 1, 0, 1;\n}\n"
    : "+f"(d[0]), "+f"(d[1]), "+f"(d[2]), "+f"(d[3]), "+f"(d[4]), "+f"(d[5]), "+f"(d[6]), "+f"(d[7]),
      "+f"(d[8]), "+f"(d[9]), "+f"(d[10]), "+f"(d[11]), "+f"(d[12]), "+f"(d[13]), "+f"(d[14]), "+f"(d[15]),
      "+f"(d[16]), "+f"(d[17]), "+f"(d[18]), "+f"(d[19]), "+f"(d[20]), "+f"(d[21]), "+f"(d[22]), "+f"(d[23]),
      "+f"(d[24]), "+f"(d[25]), "+f"(d[26]), "+f"(d[27]), "+f"(d[28]), "+f"(d[29]), "+f"(d[30]), "+f"(d[31]),
      "+f"(d[32]), "+f"(d[33]), "+f"(d[34]), "+f"(d[35]), "+f"(d[36]), "+f"(d[37]), "+f"(d[38]), "+f"(d[39]),
      "+f"(d[40]), "+f"(d[41]), "+f"(d[42]), "+f"(d[43]), "+f"(d[44]), "+f"(d[45]), "+f"(d[46]), "+f"(d[47]),
      "+f"(d[48]), "+f"(d[49]), "+f"(d[50]), "+f"(d[51]), "+f"(d[52]), "+f"(d[53]), "+f"(d[54]), "+f"(d[55]),
      "+f"(d[56]), "+f"(d[57]), "+f"(d[58]), "+f"(d[59]), "+f"(d[60]), "+f"(d[61]), "+f"(d[62]), "+f"(d[63]),
      "+f"(d[64]), "+f"(d[65]), "+f"(d[66]), "+f"(d[67]), "+f"(d[68]), "+f"(d[69]), "+f"(d[70]), "+f"(d[71]),
      "+f"(d[72]), "+f"(d[73]), "+f"(d[74]), "+f"(d[75]), "+f"(d[76]), "+f"(d[77]), "+f"(d[78]), "+f"(d[79]),
      "+f"(d[80]), "+f"(d[81]), "+f"(d[82]), "+f"(d[83]), "+f"(d[84]), "+f"(d[85]), "+f"(d[86]), "+f"(d[87]),
      "+f"(d[88]), "+f"(d[89]), "+f"(d[90]), "+f"(d[91]), "+f"(d[92]), "+f"(d[93]), "+f"(d[94]), "+f"(d[95]),
      "+f"(d[96]), "+f"(d[97]), "+f"(d[98]), "+f"(d[99]), "+f"(d[100]), "+f"(d[101]), "+f"(d[102]), "+f"(d[103]),
      "+f"(d[104]), "+f"(d[105]), "+f"(d[106]), "+f"(d[107]), "+f"(d[108]), "+f"(d[109]), "+f"(d[110]), "+f"(d[111]),
      "+f"(d[112]), "+f"(d[113]), "+f"(d[114]), "+f"(d[115]), "+f"(d[116]), "+f"(d[117]), "+f"(d[118]), "+f"(d[119]),
      "+f"(d[120]), "+f"(d[121]), "+f"(d[122]), "+f"(d[123]), "+f"(d[124]), "+f"(d[125]), "+f"(d[126]), "+f"(d[127])
    : "l"(da), "l"(db), "r"(scale_d));
}
__device__ __forceinline__ void wgmma_rs_n256_t1(float (&d)[128], uint32_t a0, uint32_t a1, uint32_t a2, uint32_t a3, uint64_t db, int scale_d) {
  asm volatile(
    "{\n.reg .pred p;\nsetp.ne.b32 p, %133, 0;\n"
    "wgmma.mma_async.sync.aligned.m64n256k16.f32.bf16.bf16 {"
    "%0, %1, %2, %3, %4, %5, %6, %7, %8, %9, %10, %11, %12, %13, %14, %15, "
    "%16, %17, %18, %19, %20, %21, %22, %23, %24, %25, %26, %27, %28, %29, %30, %31, "
    "%32, %33, %34, %35, %36, %37, %38, %39, %40, %41, %42, %43, %44, %45, %46, %47, "
    "%48, %49, %50, %51, %52, %53, %54, %55, %56, %57, %58, %59, %60, %61, %62, %63, "
    "%64, %65, %66, %67, %68, %69, %70, %71, %72, %73, %74, %75, %76, %77, %78, %79, "
    "%80, %81, %82, %83, %84, %85, %86, %87, %88, %89, %90, %91, %92, %93, %94, %95, "
    "%96, %97, %98, %99, %100, %101, %102, %103, %104, %105, %106, %107, %108, %109, %110, %111, "
    "%112, %113, %114, %115, %116, %117, %118, %119, %120, %121, %122, %123, %124, %125, %126, %127"
    "}, {%128, %129, %130, %131}, %132, p, 1, 1, 1;\n}\n"
    : "+f"(d[0]), "+f"(d[1]), "+f"(d[2]), "+f"(d[3]), "+f"(d[4]), "+f"(d[5]), "+f"(d[6]), "+f"(d[7]),
      "+f"(d[8]), "+f"(d[9]), "+f"(d[10]), "+f"(d[11]), "+f"(d[12]), "+f"(d[13]), "+f"(d[14]), "+f"(d[15]),
      "+f"(d[16]), "+f"(d[17]), "+f"(d[18]), "+f"(d[19]), "+f"(d[20]), "+f"(d[21]), "+f"(d[22]), "+f"(d[23]),
      "+f"(d[24]), "+f"(d[25]), "+f"(d[26]), "+f"(d[27]), "+f"(d[28]), "+f"(d[29]), "+f"(d[30]), "+f"(d[31]),
      "+f"(d[32]), "+f"(d[33]), "+f"(d[34]), "+f"(d[35]), "+f"(d[36]), "+f"(d[37]), "+f"(d[38]), "+f"(d[39]),
      "+f"(d[40]), "+f"(d[41]), "+f"(d[42]), "+f"(d[43]), "+f"(d[44]), "+f"(d[45]), "+f"(d[46]), "+f"(d[47]),
      "+f"(d[48]), "+f"(d[49]), "+f"(d[50]), "+f"(d[51]), "+f"(d[52]), "+f"(d[53]), "+f"(d[54]), "+f"(d[55]),
      "+f"(d[56]), "+f"(d[57]), "+f"(d[58]), "+f"(d[59]), "+f"(d[60]), "+f"(d[61]), "+f"(d[62]), "+f"(d[63]),
      "+f"(d[64]), "+f"(d[65]), "+f"(d[66]), "+f"(d[67]), "+f"(d[68]), "+f"(d[69]), "+f"(d[70]), "+f"(d[71]),
      "+f"(d[72]), "+f"(d[73]), "+f"(d[74]), "+f"(d[75]), "+f"(d[76]), "+f"(d[77]), "+f"(d[78]), "+f"(d[79]),
      "+f"(d[80]), "+f"(d[81]), "+f"(d[82]), "+f"(d[83]), "+f"(d[84]), "+f"(d[85]), "+f"(d[86]), "+f"(d[87]),
      "+f"(d[88]), "+f"(d[89]), "+f"(d[90]), "+f"(d[91]), "+f"(d[92]), "+f"(d[93]), "+f"(d[94]), "+f"(d[95]),
      "+f"(d[96]), "+f"(d[97]), "+f"(d[98]), "+f"(d[99]), "+f"(d[100]), "+f"(d[101]), "+f"(d[102]), "+f"(d[103]),
      "+f"(d[104]), "+f"(d[105]), "+f"(d[106]), "+f"(d[107]), "+f"(d[108]), "+f"(d[109]), "+f"(d[110]), "+f"(d[111]),
      "+f"(d[112]), "+f"(d[113]), "+f"(d[114]), "+f"(d[115]), "+f"(d[116]), "+f"(d[117]), "+f"(d[118]), "+f"(d[119]),
      "+f"(d[120]), "+f"(d[121]), "+f"(d[122]), "+f"(d[123]), "+f"(d[124]), "+f"(d[125]), "+f"(d[126]), "+f"(d[127])
    : "r"(a0), "r"(a1), "r"(a2), "r"(a3), "l"(db), "r"(scale_d));
}
__device__ __forceinline__ void wgmma_ss_n96_t1(float (&d)[48], uint64_t da, uint64_t db, int scale_d) {
  asm volatile(
    "{\n.reg .pred p;\nsetp.ne.b32 p, %50, 0;\n"
    "wgmma.mma_async.sync.aligned.m64n96k16.f32.bf16.bf16 {"
    "%0, %1, %2, %3, %4, %5, %6, %7, %8, %9, %10, %11, %12, %13, %14, %15, "
    "%16, %17, %18, %19, %20, %21, %22, %23, %24, %25, %26, %27, %28, %29, %30, %31, "
    "%32, %33, %34, %35, %36, %37, %38, %39, %40, %41, %42, %43, %44, %45, %46, %47"
    "}, %48, %49, p, 1, 1, 0, 1;\n}\n"
    : "+f"(d[0]), "+f"(d[1]), "+f"(d[2]), "+f"(d[3]), "+f"(d[4]), "+f"(d[5]), "+f"(d[6]), "+f"(d[7]),
      "+f"(d[8]), "+f"(d[9]), "+f"(d[10]), "+f"(d[11]), "+f"(d[12]), "+f"(d[13]), "+f"(d[14]), "+f"(d[15]),
      "+f"(d[16]), "+f"(d[17]), "+f"(d[18]), "+f"(d[19]), "+f"(d[20]), "+f"(d[21]), "+f"(d[22]), "+f"(d[23]),
      "+f"(d[24]), "+f"(d[25]), "+f"(d[26]), "+f"(d[27]), "+f"(d[28]), "+f"(d[29]), "+f"(d[30]), "+f"(d[31]),
      "+f"(d[32]), "+f"(d[33]), "+f"(d[34]), "+f"(d[35]), "+f"(d[36]), "+f"(d[37]), "+f"(d[38]), "+f"(d[39]),
      "+f"(d[40]), "+f"(d[41]), "+f"(d[42]), "+f"(d[43]), "+f"(d[44]), "+f"(d[45]), "+f"(d[46]), "+f"(d[47])
    : "l"(da), "l"(db), "r"(scale_d));
}

#define TS(k)

constexpr int B_PP = 1;
constexpr int B_CONS = 3;
constexpr int B_WG = 4;
constexpr int B_AUX = 6;

__global__ void __cluster_dims__(2, 1, 1) __launch_bounds__(384, 1)
fused_kernel(const __grid_constant__ Maps mp, const __nv_bfloat16* __restrict__ x, const __nv_bfloat16* __restrict__ kc,
             const __nv_bfloat16* __restrict__ wo, const __nv_bfloat16* __restrict__ wg, const __nv_bfloat16* __restrict__ wu,
             const __nv_bfloat16* __restrict__ wd, const __nv_bfloat16* __restrict__ cvec, const __nv_bfloat16* __restrict__ wmod,
             __nv_bfloat16* __restrict__ out) {
  extern __shared__ __align__(1024) uint8_t sm_raw[];
  const uint32_t sb = smem_u32(sm_raw);
  const int tid = threadIdx.x, lane = tid & 31;
  const int b = blockIdx.x;
  const uint32_t rank = b & 1;
  const int g = (b >> 1) & 7;
  const int rt = (b >> 4) * 2 + rank;
  auto FULL = [&](int s) { return sb + OFF_BAR + 8 * s; };
  auto EMPTY = [&](int s) { return sb + OFF_BAR + 56 + 8 * s; };

  if (tid == 0) {
    asm volatile("{\n.reg .pred p;\nsetp.ne.u32 p, %0, 0;\n@p trap;\n}" :: "r"(sb & 1023));
    for (int s = 0; s < 7; s++) { mbar_init(FULL(s), 1); mbar_init(EMPTY(s), 16); }
    asm volatile("fence.mbarrier_init.release.cluster;" ::: "memory");
  }
  __syncwarp();
  asm volatile("barrier.cluster.arrive.relaxed.aligned;" ::: "memory");

  if (tid < 128) {
    asm volatile("setmaxnreg.dec.sync.aligned.u32 %0;" :: "n"(PROD_REGS));
    asm volatile("barrier.cluster.wait.aligned;" ::: "memory");
    if (tid == 0) {
      uint32_t pe = 0x70;
      auto acquire = [&](int s) { mbar_wait(EMPTY(s), (pe >> s) & 1); pe ^= 1u << s; mbar_expect_tx(FULL(s), SLOT); };
      auto load4 = [&](int s, const CUtensorMap* m, int xx, int yy) {
        tma_load_mc(sb + s * SLOT + rank * 16384, m, FULL(s), xx, yy);
        tma_load_mc(sb + s * SLOT + rank * 16384 + 8192, m, FULL(s), xx + 64, yy);
      };
      int s3 = 4;
      for (int i = 0; i < 16; i++) {
        acquire(s3);
        load4(s3, &mp.wq, g * 512 + (i < 8 ? 256 : 0) + rank * 128, (i & 7) * 64);
        s3 = s3 == 6 ? 4 : s3 + 1;
        if (i == 2) {
          for (int j = 0; j < 4; j++) tma_prefetch(&mp.wq, g * 512 + (rt < 8 ? 256 : 0) + j * 64, (rt & 7) * 64);
          desc_prefetch(&mp.k); desc_prefetch(&mp.v);
        }
        if (i == 3) {
          tma_prefetch(&mp.k, 0, g * SEQ + rt * 128); tma_prefetch(&mp.k, 64, g * SEQ + rt * 128);
          tma_prefetch(&mp.v, 0, g * SEQ + rt * 128); tma_prefetch(&mp.v, 64, g * SEQ + rt * 128);
        }
      }
      for (int t = 0; t <= 64; t++) {
        if (t < 64) { const int s = 5 + (t & 1); acquire(s); tma_load_mc(sb + s * SLOT + rank * 16384, &mp.k, FULL(s), rank * 64, g * SEQ + (t & 15) * 128); }
        if (t > 0) { const int s = 3 + (t & 1); acquire(s); tma_load_mc(sb + s * SLOT + rank * 16384, &mp.v, FULL(s), rank * 64, g * SEQ + ((t - 1) & 15) * 128); }
      }
      for (int i = 0; i < 16; i++) {
        const int s = (0x3465 >> ((i & 3) * 4)) & 7;
        acquire(s);
        load4(s, &mp.wo, (i >> 3) * 256 + rank * 128, g * 512 + (i & 7) * 64);
      }
      s3 = 5;
      for (int i = 0; i < 24; i++) {
        acquire(s3);
        if (i < 16) load4(s3, rank ? &mp.wu : &mp.wg, g * FS + (i >> 3) * 128, (i & 7) * 64);
        else load4(s3, &mp.wd, ((i - 16) >> 2) * 256 + rank * 128, g * FS + (i & 3) * 64);
        s3 = s3 == 6 ? 4 : s3 + 1;
        if (i == 2) {
          const uint32_t tag = lds32(sb + OFF_EPOCH);
          cnt_wait(&g_cnt[(16 + rt) * 32], tag * 8);
          fence_async_all();
          for (int s = 0; s < 4; s++) {
            mbar_expect_tx(FULL(s), SLOT);
            tma_load(sb + s * SLOT, &mp.h2, FULL(s), s * 128, rt * 128);
            tma_load(sb + s * SLOT + 16384, &mp.h2, FULL(s), s * 128 + 64, rt * 128);
          }
        }
      }
    } else if (tid >= 32) {
      const int j = tid - 32;
      mbar_wait(FULL(3), 0);
      if (j == 0) {
        bulk_prefetch((const uint8_t*)wo + (size_t)b * 32768, 32768);
        bulk_prefetch((const uint8_t*)wg + (size_t)b * 14336, 14336);
        bulk_prefetch((const uint8_t*)wu + (size_t)b * 14336, 14336);
        bulk_prefetch((const uint8_t*)wd + (size_t)b * 14336, 14336);
      }
      float a[8];
#pragma unroll
      for (int i = 0; i < 8; i++) a[i] = 0.f;
#pragma unroll 2
      for (int k = j >> 1; k < 512; k += 48) {
        const uint4 w = ldg_nc128(wmod + (size_t)k * 3072 + 1024 + b * 16 + (j & 1) * 8);
        const float sc = silu_bf(__bfloat162float(cvec[k]));
        a[0] += sc * blo(w.x); a[1] += sc * bhi(w.x); a[2] += sc * blo(w.y); a[3] += sc * bhi(w.y);
        a[4] += sc * blo(w.z); a[5] += sc * bhi(w.z); a[6] += sc * blo(w.w); a[7] += sc * bhi(w.w);
      }
#pragma unroll
      for (int i = 0; i < 8; i++) {
#pragma unroll
        for (int o = 2; o < 32; o <<= 1) a[i] += __shfl_xor_sync(~0u, a[i], o);
      }
      if (lane < 2) {
#pragma unroll
        for (int i = 0; i < 8; i++) sts32(sb + OFF_RED2 + ((j >> 5) * 16 + lane * 8 + i) * 4, __float_as_uint(a[i]));
      }
      bar_sync(B_AUX, 96);
      if (j < 8) {
        float v0 = 0.f, v1 = 0.f;
#pragma unroll
        for (int w = 0; w < 3; w++) { v0 += __uint_as_float(lds32(sb + OFF_RED2 + (w * 16 + 2 * j) * 4)); v1 += __uint_as_float(lds32(sb + OFF_RED2 + (w * 16 + 2 * j + 1) * 4)); }
        st_ll(&g_modll[512 + b * 8 + j], pack2(v0, v1), lds32(sb + OFF_EPOCH));
      }
    }
  } else {
    asm volatile("setmaxnreg.inc.sync.aligned.u32 %0;" :: "n"(CONS_REGS));
    const int ct = tid - 128, cw = ct >> 7, wid = ct >> 5;
    uint32_t rel0;
    asm volatile("mapa.shared::cluster.u32 %0, %1, %2;" : "=r"(rel0) : "r"(EMPTY(0)), "r"(lane & 1));
    auto release = [&](int s) { if (lane < 2) asm volatile("mbarrier.arrive.shared::cluster.b64 _, [%0];" :: "r"(rel0 + 8 * s) : "memory"); };
    const uint32_t frag_row = wid * 16 + (lane & 15);
    auto frag_addr = [&](int slot, int kk) { return sb + slot * SLOT + (kk >> 2) * 16384 + frag_row * 128 + ((((kk & 3) * 2 + (lane >> 4)) ^ (lane & 7)) << 4); };
    uint32_t tag;
    TS(31);

    {
      asm volatile("ld.relaxed.gpu.global.u32 %0, [%1];" : "=r"(tag) : "l"(&g_epoch) : "memory");
      const uint4 w0 = ldg_nc128(wmod + (size_t)ct * 3072 + b * 8), w1 = ldg_nc128(wmod + (size_t)(ct + 256) * 3072 + b * 8);
      const float c0 = __bfloat162float(cvec[ct]), c1 = __bfloat162float(cvec[ct + 256]);
      uint32_t xr[128];
      const __nv_bfloat16* xp = x + (size_t)(rt * 128 + wid * 16) * DM + lane * 8;
#pragma unroll
      for (int i = 0; i < 16; i++) {
        const uint4 u = ldg_nc128(xp + i * DM), v = ldg_nc128(xp + i * DM + 256);
        xr[8 * i] = u.x; xr[8 * i + 1] = u.y; xr[8 * i + 2] = u.z; xr[8 * i + 3] = u.w;
        xr[8 * i + 4] = v.x; xr[8 * i + 5] = v.y; xr[8 * i + 6] = v.z; xr[8 * i + 7] = v.w;
      }
      tag += 1;
      if (ct == 0) sts32(sb + OFF_EPOCH, tag);
      {
        const float s0 = silu_bf(c0), s1 = silu_bf(c1);
        float a[8] = {s0 * blo(w0.x) + s1 * blo(w1.x), s0 * bhi(w0.x) + s1 * bhi(w1.x), s0 * blo(w0.y) + s1 * blo(w1.y), s0 * bhi(w0.y) + s1 * bhi(w1.y),
                      s0 * blo(w0.z) + s1 * blo(w1.z), s0 * bhi(w0.z) + s1 * bhi(w1.z), s0 * blo(w0.w) + s1 * blo(w1.w), s0 * bhi(w0.w) + s1 * bhi(w1.w)};
#pragma unroll
        for (int i = 0; i < 4; i++) { const bool up = lane & 16; const float snd = up ? a[i] : a[i + 4], kp = up ? a[i + 4] : a[i]; a[i] = kp + __shfl_xor_sync(~0u, snd, 16); }
#pragma unroll
        for (int i = 0; i < 2; i++) { const bool up = lane & 8; const float snd = up ? a[i] : a[i + 2], kp = up ? a[i + 2] : a[i]; a[i] = kp + __shfl_xor_sync(~0u, snd, 8); }
        { const bool up = lane & 4; const float snd = up ? a[0] : a[1], kp = up ? a[1] : a[0]; a[0] = kp + __shfl_xor_sync(~0u, snd, 4); }
        a[0] += __shfl_xor_sync(~0u, a[0], 2); a[0] += __shfl_xor_sync(~0u, a[0], 1);
        if ((lane & 3) == 0) sts32(sb + OFF_RED + (wid * 8 + (lane >> 2)) * 4, __float_as_uint(a[0]));
        bar_sync(B_CONS, 256);
        if (ct < 4) {
          float v0 = 0.f, v1 = 0.f;
#pragma unroll
          for (int w = 0; w < 8; w++) { v0 += __uint_as_float(lds32(sb + OFF_RED + (w * 8 + 2 * ct) * 4)); v1 += __uint_as_float(lds32(sb + OFF_RED + (w * 8 + 2 * ct + 1) * 4)); }
          st_ll(&g_modll[b * 4 + ct], pack2(v0, v1), tag);
        }
      }
      TS(0);
      float v[32];
#pragma unroll
      for (int i = 0; i < 16; i++) {
        float s = 0.f, q = 0.f;
#pragma unroll
        for (int j = 0; j < 8; j++) { const float lo = blo(xr[8 * i + j]), hi = bhi(xr[8 * i + j]); s += lo; s += hi; q = fmaf(lo, lo, q); q = fmaf(hi, hi, q); }
        v[2 * i] = s; v[2 * i + 1] = q;
      }
      xreduce<16>(v, lane); xreduce<8>(v, lane); xreduce<4>(v, lane); xreduce<2>(v, lane); xreduce<1>(v, lane);
      float rs, nm;
      {
        const float oth = __shfl_xor_sync(~0u, v[0], 1);
        const float mean = ((lane & 1) ? oth : v[0]) * (1.f / DM), ex = ((lane & 1) ? v[0] : oth) * (1.f / DM);
        const float var = fmaxf(ex - mean * mean, 0.f);
        rs = 1.f / bround(sqrtf(bround(bround(var) + 1e-5f)));
        nm = -bround(mean) * rs;
      }
#pragma unroll
      for (int i = 0; i < 16; i++) {
        const float r = __shfl_sync(~0u, rs, 2 * i), m = __shfl_sync(~0u, nm, 2 * i);
#pragma unroll
        for (int j = 0; j < 8; j++) xr[8 * i + j] = pack2(fmaf(blo(xr[8 * i + j]), r, m), fmaf(bhi(xr[8 * i + j]), r, m));
      }
      pin(xr);
      TS(1);
      {
        const unsigned long long pa = ld_ll(&g_modll[ct]), pc = ld_ll(&g_modll[256 + ct]);
        sts32(sb + OFF_MODSM + ct * 4, get_ll(&g_modll[ct], pa, tag));
        sts32(sb + OFF_MODSM + 1024 + ct * 4, one_plus(get_ll(&g_modll[256 + ct], pc, tag)));
      }
      bar_sync(B_CONS, 256);
      TS(2);
      const uint4 sa0 = lds128(sb + OFF_MODSM + lane * 16), sa1 = lds128(sb + OFF_MODSM + 512 + lane * 16);
      const uint4 ga0 = lds128(sb + OFF_MODSM + 1024 + lane * 16), ga1 = lds128(sb + OFF_MODSM + 1536 + lane * 16);
#pragma unroll
      for (int i = 0; i < 16; i++) {
        const uint32_t row = wid * 16 + i;
        const uint32_t ad = sb + (lane >> 3) * 16384 + row * 128 + (((lane & 7) ^ (i & 7)) << 4);
        const uint32_t h0 = hfma2(xr[8 * i], ga0.x, sa0.x), h1 = hfma2(xr[8 * i + 1], ga0.y, sa0.y), h2 = hfma2(xr[8 * i + 2], ga0.z, sa0.z), h3 = hfma2(xr[8 * i + 3], ga0.w, sa0.w);
        const uint32_t h4 = hfma2(xr[8 * i + 4], ga1.x, sa1.x), h5 = hfma2(xr[8 * i + 5], ga1.y, sa1.y), h6 = hfma2(xr[8 * i + 6], ga1.z, sa1.z), h7 = hfma2(xr[8 * i + 7], ga1.w, sa1.w);
        sts128(ad, h0, h1, h2, h3);
        sts128(ad + 65536, h4, h5, h6, h7);
      }
      fence_async_smem();
      bar_sync(B_WG + cw, 128);
    }
    asm volatile("barrier.cluster.wait.aligned;" ::: "memory");
    TS(3);

    const uint64_t dA0 = make_desc(sb + cw * 8192, 16, 1024);
    const uint64_t dB0 = make_desc(sb, 8192, 1024);
    uint32_t q[32];

    {
      uint32_t held[64];
      float acc[128];
      int s3 = 4, prev = 4;
      uint32_t pf = 0;
#pragma unroll
      for (int pass = 0; pass < 2; pass++) {
#pragma unroll 1
        for (int k = 0; k < 8; k++) {
          mbar_wait(FULL(s3), (pf >> s3) & 1); pf ^= 1u << s3;
          wg_fence();
#pragma unroll
          for (int ks = 0; ks < 4; ks++) wgmma_ss_n256_t1(acc, dA0 + k * 1024 + ks * 2, dB0 + s3 * 2048 + ks * 128, (k | ks) != 0);
          wg_commit();
          if (k > 0) { wg_wait<1>(); release(prev); }
          prev = s3; s3 = s3 == 6 ? 4 : s3 + 1;
        }
        wg_wait<0>(); pin(acc);
        release(prev);
        if (pass == 0) {
#pragma unroll
          for (int j = 0; j < 64; j++) held[j] = pack2(acc[2 * j], acc[2 * j + 1]);
          pin(held);
        }
      }
      release(3);
#pragma unroll
      for (int j = 0; j < 32; j++) q[j] = pack2(acc[2 * j], acc[2 * j + 1]);
#pragma unroll
      for (int kk = 0; kk < 8; kk++) {
        stsm4(frag_addr(0, kk), pack2(acc[64 + 8 * kk], acc[65 + 8 * kk]), pack2(acc[66 + 8 * kk], acc[67 + 8 * kk]), pack2(acc[68 + 8 * kk], acc[69 + 8 * kk]), pack2(acc[70 + 8 * kk], acc[71 + 8 * kk]));
        stsm4(frag_addr(1, kk), held[4 * kk], held[4 * kk + 1], held[4 * kk + 2], held[4 * kk + 3]);
        stsm4(frag_addr(2, kk), held[32 + 4 * kk], held[33 + 4 * kk], held[34 + 4 * kk], held[35 + 4 * kk]);
      }
      pin(q);
    }
    TS(4);

    {
      const float cl2 = 0.08838834764831845f * 1.4426950408889634f;
      const uint64_t dK0 = make_desc(sb + 5 * SLOT, 16, 1024);
      const uint64_t dV0 = make_desc(sb + 3 * SLOT, 16384, 1024);
      float o[64], s[64];
      uint32_t p[32];
      float ms0, ms1, l0, l1, t0, t1;
      auto qk = [&](int st) {
#pragma unroll
        for (int kk = 0; kk < 8; kk++) wgmma_rs_n128_t0(s, q[4 * kk], q[4 * kk + 1], q[4 * kk + 2], q[4 * kk + 3], dK0 + st * 2048 + (kk >> 2) * 1024 + (kk & 3) * 2, kk != 0);
        wg_commit();
      };
      auto pv = [&](int st, int acc) {
#pragma unroll
        for (int kk = 0; kk < 8; kk++) wgmma_rs_n128_t1(o, p[4 * kk], p[4 * kk + 1], p[4 * kk + 2], p[4 * kk + 3], dV0 + st * 2048 + kk * 128, (kk != 0) | acc);
        wg_commit();
      };
      auto rowmax = [&](float& a, float& c) {
        float u[4], w[4];
#pragma unroll
        for (int j = 0; j < 4; j++) { u[j] = fmaxf(s[4 * j], s[4 * j + 1]); w[j] = fmaxf(s[4 * j + 2], s[4 * j + 3]); }
#pragma unroll
        for (int j = 4; j < 16; j++) { u[j & 3] = fmaxf(fmaxf(u[j & 3], s[4 * j]), s[4 * j + 1]); w[j & 3] = fmaxf(fmaxf(w[j & 3], s[4 * j + 2]), s[4 * j + 3]); }
        float x0 = fmaxf(fmaxf(u[0], u[1]), fmaxf(u[2], u[3])), x1 = fmaxf(fmaxf(w[0], w[1]), fmaxf(w[2], w[3]));
        x0 = fmaxf(x0, __shfl_xor_sync(~0u, x0, 1)); x1 = fmaxf(x1, __shfl_xor_sync(~0u, x1, 1));
        x0 = fmaxf(x0, __shfl_xor_sync(~0u, x0, 2)); x1 = fmaxf(x1, __shfl_xor_sync(~0u, x1, 2));
        a = x0 * cl2; c = x1 * cl2;
      };
      auto exprange = [&](auto j0, auto j1) {
#pragma unroll
        for (int j = j0; j < j1; j++) {
          s[4 * j] = ex2(fmaf(s[4 * j], cl2, -ms0)); s[4 * j + 1] = ex2(fmaf(s[4 * j + 1], cl2, -ms0));
          s[4 * j + 2] = ex2(fmaf(s[4 * j + 2], cl2, -ms1)); s[4 * j + 3] = ex2(fmaf(s[4 * j + 3], cl2, -ms1));
          if (j == 0) { t0 = s[0] + s[1]; t1 = s[2] + s[3]; } else { t0 += s[4 * j] + s[4 * j + 1]; t1 += s[4 * j + 2] + s[4 * j + 3]; }
        }
      };
      auto expsum = [&]() { exprange(IC<0>(), IC<16>()); };
      auto cvtp = [&]() {
#pragma unroll
        for (int j = 0; j < 32; j++) p[j] = pack2(s[2 * j], s[2 * j + 1]);
      };
      auto inv_l = [&](float& i0, float& i1) {
        float a = l0 + __shfl_xor_sync(~0u, l0, 1), c = l1 + __shfl_xor_sync(~0u, l1, 1);
        a += __shfl_xor_sync(~0u, a, 2); c += __shfl_xor_sync(~0u, c, 2);
        i0 = 1.f / a; i1 = 1.f / c;
      };
      if (cw == 0) bar_arrive(B_PP, 256);
      mbar_wait(FULL(5), 1);
      bar_sync(B_PP + cw, 256);
      wg_fence();
      qk(0);
      bar_arrive(B_PP + (cw ^ 1), 256);
      wg_wait<0>(); pin(s);
      release(5);
      rowmax(ms0, ms1);
      expsum();
      cvtp();
      l0 = t0; l1 = t1;
      pin(p);
      mbar_wait(FULL(6), 1);
      TS(5);
#pragma unroll 1
      for (int t = 1; t < 64; t++) {
        const int st = t & 1;
        bar_sync(B_PP + cw, 256);
        wg_fence();
        qk(st);
        mbar_wait(FULL(3 + st), ((t - 1) >> 1) & 1);
        wg_fence();
        pv(st, (t & 15) != 1);
        bar_arrive(B_PP + (cw ^ 1), 256);
        wg_wait<1>(); pin(s);
        release(5 + st);
        const bool first = (t & 15) == 0;
        float i0, i1;
        if (first) { inv_l(i0, i1); rowmax(ms0, ms1); l0 = 0.f; l1 = 0.f; }
        exprange(IC<0>(), IC<EXP_SPLIT>());
        pin(s);
        mbar_wait(FULL(6 - st), (((t + 1) >> 1) & 1) ^ 1);
        wg_wait<0>(); pin(o); pin(p);
        release(3 + st);
        exprange(IC<EXP_SPLIT>(), IC<16>());
        if (first) {
          const int slot = (t >> 4) - 1;
#pragma unroll
          for (int j = 0; j < 16; j++) { p[2 * j] = pack2(o[4 * j] * i0, o[4 * j + 1] * i0); p[2 * j + 1] = pack2(o[4 * j + 2] * i1, o[4 * j + 3] * i1); }
#pragma unroll
          for (int kk = 0; kk < 8; kk++) stsm4(frag_addr(slot, kk), p[4 * kk], p[4 * kk + 1], p[4 * kk + 2], p[4 * kk + 3]);
          fence_async_smem();
        }
        cvtp();
        if (__any_sync(~0u, !(t0 + t1 <= 1.2089258e24f))) {
          const uint32_t* kp = (const uint32_t*)(kc + (size_t)(g * SEQ + (t & 15) * 128 + (lane >> 2)) * DH) + (lane & 3);
#pragma unroll
          for (int j = 0; j < 16; j++) {
            s[4 * j] = 0.f; s[4 * j + 1] = 0.f; s[4 * j + 2] = 0.f; s[4 * j + 3] = 0.f;
#pragma unroll
            for (int kk = 0; kk < 8; kk++)
              mma16816(s[4 * j], s[4 * j + 1], s[4 * j + 2], s[4 * j + 3], q[4 * kk], q[4 * kk + 1], q[4 * kk + 2], q[4 * kk + 3], ldg_nc32(kp + j * 512 + kk * 8), ldg_nc32(kp + j * 512 + kk * 8 + 4));
          }
          float x0, x1;
          rowmax(x0, x1);
          x0 = fmaxf(x0, ms0); x1 = fmaxf(x1, ms1);
          const float a0 = ex2(ms0 - x0), a1 = ex2(ms1 - x1);
          ms0 = x0; ms1 = x1; l0 *= a0; l1 *= a1;
#pragma unroll
          for (int j = 0; j < 16; j++) { o[4 * j] *= a0; o[4 * j + 1] *= a0; o[4 * j + 2] *= a1; o[4 * j + 3] *= a1; }
          expsum();
          cvtp();
        }
        l0 += t0; l1 += t1;
        if ((t & 15) == 15 && t < 63) {
#pragma unroll
          for (int kk = 0; kk < 8; kk++) ldsm4(frag_addr(t >> 4, kk), q[4 * kk], q[4 * kk + 1], q[4 * kk + 2], q[4 * kk + 3]);
        }
        pin(p); pin(o); pin(q);
        asm volatile("" : "+f"(l0), "+f"(l1) :: "memory");
      }
      mbar_wait(FULL(3), 1);
      if (cw == 0) bar_sync(B_PP, 256);
      wg_fence();
      pv(0, 1);
      float i0, i1;
      inv_l(i0, i1);
      wg_wait<0>(); pin(o);
      release(3);
#pragma unroll
      for (int j = 0; j < 16; j++) { q[2 * j] = pack2(o[4 * j] * i0, o[4 * j + 1] * i0); q[2 * j + 1] = pack2(o[4 * j + 2] * i1, o[4 * j + 3] * i1); }
      pin(q);
    }
    TS(10);

    uint4* const part_w = g_part + ((size_t)(rt * 8 + wid) * 8 + g) * 1024 + lane;
    const uint4* const part_r = g_part + (size_t)(rt * 8 + g) * 8 * 1024 + wid * 128 + lane;
    auto store_part = [&](const float (&acc)[128], int pass) {
#pragma unroll
      for (int c = 0; c < 16; c++)
        stg128(part_w + (pass * 16 + c) * 32, pack2(acc[8 * c], acc[8 * c + 1]), pack2(acc[8 * c + 2], acc[8 * c + 3]), pack2(acc[8 * c + 4], acc[8 * c + 5]), pack2(acc[8 * c + 6], acc[8 * c + 7]));
    };
    auto exchange = [&](int phase) {
      fence_gpu();
      bar_sync(B_CONS, 256);
      if (ct == 0) { cnt_signal(&g_cnt[(phase * 16 + rt) * 32]); cnt_wait(&g_cnt[(phase * 16 + rt) * 32], tag * 8); }
      bar_sync(B_CONS, 256);
    };
    auto gather = [&](float (&y)[32]) {
#pragma unroll
      for (int h = 0; h < 2; h++) {
        uint4 u[16];
#pragma unroll
        for (int sg = 0; sg < 4; sg++)
#pragma unroll
          for (int c = 0; c < 4; c++) u[sg * 4 + c] = ldg_cg128(part_r + (h * 4 + sg) * 1024 + c * 32);
#pragma unroll
        for (int sg = 0; sg < 4; sg++)
#pragma unroll
          for (int c = 0; c < 4; c++) {
            const uint4 w = u[sg * 4 + c];
            if (h == 0 && sg == 0) {
              y[8 * c] = blo(w.x); y[8 * c + 1] = bhi(w.x); y[8 * c + 2] = blo(w.y); y[8 * c + 3] = bhi(w.y);
              y[8 * c + 4] = blo(w.z); y[8 * c + 5] = bhi(w.z); y[8 * c + 6] = blo(w.w); y[8 * c + 7] = bhi(w.w);
            } else {
              y[8 * c] += blo(w.x); y[8 * c + 1] += bhi(w.x); y[8 * c + 2] += blo(w.y); y[8 * c + 3] += bhi(w.y);
              y[8 * c + 4] += blo(w.z); y[8 * c + 5] += bhi(w.z); y[8 * c + 6] += blo(w.w); y[8 * c + 7] += bhi(w.w);
            }
          }
      }
    };
    auto write_rows = [&](const uint32_t (&w)[16], __nv_bfloat16* dst) {
#pragma unroll
      for (int c = 0; c < 4; c++) stsm4(sb + (lane & 15) * STG_PITCH + (wid * 64 + c * 16 + (lane >> 4) * 8) * 2, w[4 * c], w[4 * c + 1], w[4 * c + 2], w[4 * c + 3]);
      fence_async_smem();
      bar_sync(B_CONS, 256);
      if (ct < 16) {
        bulk_store(dst + (size_t)(rt * 128 + g * 16 + ct) * DM, sb + ct * STG_PITCH, 1024);
        asm volatile("cp.async.bulk.commit_group;" ::: "memory");
      }
    };
    const int mcol = wid * 32 + (lane & 3);

    {
      float acc[128];
#pragma unroll 1
      for (int pass = 0; pass < 2; pass++) {
        int prev = 0;
#pragma unroll 1
        for (int k = 0; k < 6; k++) {
          const int s = (0x3465 >> ((k & 3) * 4)) & 7;
          mbar_wait(FULL(s), ((k >> 2) & 1) ^ (s >= 5));
          wg_fence();
#pragma unroll
          for (int ks = 0; ks < 4; ks++) wgmma_ss_n256_t1(acc, dA0 + k * 1024 + ks * 2, dB0 + s * 2048 + ks * 128, (k | ks) != 0);
          wg_commit();
          if (k > 0) { wg_wait<1>(); release(prev); }
          prev = s;
        }
        mbar_wait(FULL(4), 1);
        wg_fence();
#pragma unroll
        for (int ks = 0; ks < 4; ks++) wgmma_rs_n256_t1(acc, q[4 * ks], q[4 * ks + 1], q[4 * ks + 2], q[4 * ks + 3], dB0 + 4 * 2048 + ks * 128, 1);
        wg_commit();
        wg_wait<1>(); release(6);
        mbar_wait(FULL(3), 1);
        wg_fence();
#pragma unroll
        for (int ks = 0; ks < 4; ks++) wgmma_rs_n256_t1(acc, q[16 + 4 * ks], q[17 + 4 * ks], q[18 + 4 * ks], q[19 + 4 * ks], dB0 + 3 * 2048 + ks * 128, 1);
        wg_commit();
        wg_wait<1>(); release(4);
        wg_wait<0>(); pin(acc); pin(q);
        if (pass == 0) release(3);
        store_part(acc, pass);
      }
    }
    TS(11);

    uint32_t x1[16];
    {
      uint32_t ga[8], cb[8], sbv[8];
      {
        unsigned long long pg[8], ps[8], pc[8];
#pragma unroll
        for (int j = 0; j < 8; j++) { pg[j] = ld_ll(&g_modll[512 + mcol + 4 * j]); ps[j] = ld_ll(&g_modll[768 + mcol + 4 * j]); pc[j] = ld_ll(&g_modll[1024 + mcol + 4 * j]); }
        const uint32_t* xp = (const uint32_t*)(x + (size_t)(rt * 128 + g * 16 + (lane >> 2)) * DM) + mcol;
#pragma unroll
        for (int j = 0; j < 8; j++) { x1[2 * j] = ldg_nc32(xp + 4 * j); x1[2 * j + 1] = ldg_nc32(xp + 8 * (DM / 2) + 4 * j); }
#pragma unroll
        for (int j = 0; j < 8; j++) {
          ga[j] = get_ll(&g_modll[512 + mcol + 4 * j], pg[j], tag); sbv[j] = get_ll(&g_modll[768 + mcol + 4 * j], ps[j], tag);
          cb[j] = one_plus(get_ll(&g_modll[1024 + mcol + 4 * j], pc[j], tag));
        }
      }
      exchange(0);
      TS(12);
      float y[32];
      gather(y);
      float s0 = 0.f, q0 = 0.f, s1 = 0.f, q1 = 0.f;
#pragma unroll
      for (int j = 0; j < 8; j++) {
        x1[2 * j] = pack2(fmaf(blo(ga[j]), y[4 * j], blo(x1[2 * j])), fmaf(bhi(ga[j]), y[4 * j + 1], bhi(x1[2 * j])));
        x1[2 * j + 1] = pack2(fmaf(blo(ga[j]), y[4 * j + 2], blo(x1[2 * j + 1])), fmaf(bhi(ga[j]), y[4 * j + 3], bhi(x1[2 * j + 1])));
        y[4 * j] = blo(x1[2 * j]); y[4 * j + 1] = bhi(x1[2 * j]); y[4 * j + 2] = blo(x1[2 * j + 1]); y[4 * j + 3] = bhi(x1[2 * j + 1]);
        s0 += y[4 * j] + y[4 * j + 1]; q0 = fmaf(y[4 * j], y[4 * j], q0); q0 = fmaf(y[4 * j + 1], y[4 * j + 1], q0);
        s1 += y[4 * j + 2] + y[4 * j + 3]; q1 = fmaf(y[4 * j + 2], y[4 * j + 2], q1); q1 = fmaf(y[4 * j + 3], y[4 * j + 3], q1);
      }
#pragma unroll
      for (int o = 1; o < 4; o <<= 1) { s0 += __shfl_xor_sync(~0u, s0, o); q0 += __shfl_xor_sync(~0u, q0, o); s1 += __shfl_xor_sync(~0u, s1, o); q1 += __shfl_xor_sync(~0u, q1, o); }
      if ((lane & 3) == 0) sts128(sb + OFF_MODSM + (wid * 8 + (lane >> 2)) * 16, __float_as_uint(s0), __float_as_uint(q0), __float_as_uint(s1), __float_as_uint(q1));
      bar_sync(B_CONS, 256);
      s0 = q0 = s1 = q1 = 0.f;
#pragma unroll
      for (int w = 0; w < 8; w++) { const uint4 u = lds128(sb + OFF_MODSM + (w * 8 + (lane >> 2)) * 16); s0 += __uint_as_float(u.x); q0 += __uint_as_float(u.y); s1 += __uint_as_float(u.z); q1 += __uint_as_float(u.w); }
      const float m0 = s0 * (1.f / DM), m1 = s1 * (1.f / DM);
      const float r0 = 1.f / bround(sqrtf(bround(bround(fmaxf(q0 * (1.f / DM) - m0 * m0, 0.f)) + 1e-5f)));
      const float r1 = 1.f / bround(sqrtf(bround(bround(fmaxf(q1 * (1.f / DM) - m1 * m1, 0.f)) + 1e-5f)));
      const float n0 = -bround(m0) * r0, n1 = -bround(m1) * r1;
      uint32_t hw[16];
#pragma unroll
      for (int j = 0; j < 8; j++) {
        hw[2 * j] = hfma2(pack2(fmaf(y[4 * j], r0, n0), fmaf(y[4 * j + 1], r0, n0)), cb[j], sbv[j]);
        hw[2 * j + 1] = hfma2(pack2(fmaf(y[4 * j + 2], r1, n1), fmaf(y[4 * j + 3], r1, n1)), cb[j], sbv[j]);
      }
      write_rows(hw, g_h2);
      if (wid == 0) {
        asm volatile("cp.async.bulk.wait_group 0;" ::: "memory");
        fence_async_all();
        fence_gpu();
        __syncwarp();
        if (lane == 0) cnt_signal(&g_cnt[(16 + rt) * 32]);
      }
      pin(x1);
    }
    TS(13);

    {
      uint32_t act[56];
      int s3 = 5, prev = 5;
      uint32_t pf = 0x60;
      auto swiglu = [&](float gt0, float gt1, float up0, float up1) {
        const float h0 = 0.5f * gt0, h1 = 0.5f * gt1;
        return pack2(fmaf(h0, tanh_fast(h0), h0) * up0, fmaf(h1, tanh_fast(h1), h1) * up1);
      };
      {
        float acc[128];
#pragma unroll 1
        for (int k = 0; k < 8; k++) {
          if ((k & 1) == 0) mbar_wait(FULL(k >> 1), k == 6 ? 0 : 0);
          mbar_wait(FULL(s3), (pf >> s3) & 1); pf ^= 1u << s3;
          wg_fence();
#pragma unroll
          for (int ks = 0; ks < 4; ks++) wgmma_ss_n256_t1(acc, dA0 + k * 1024 + ks * 2, dB0 + s3 * 2048 + ks * 128, (k | ks) != 0);
          wg_commit();
          if (k > 0) { wg_wait<1>(); release(prev); }
          prev = s3; s3 = s3 == 6 ? 4 : s3 + 1;
          if (k == 0) TS(14);
        }
        wg_wait<0>(); pin(acc);
        release(prev);
#pragma unroll
        for (int j = 0; j < 32; j++) act[j] = swiglu(acc[2 * j], acc[2 * j + 1], acc[64 + 2 * j], acc[65 + 2 * j]);
      }
      {
        float ag[48], au[48];
#pragma unroll 1
        for (int k = 0; k < 8; k++) {
          mbar_wait(FULL(s3), (pf >> s3) & 1); pf ^= 1u << s3;
          wg_fence();
#pragma unroll
          for (int ks = 0; ks < 4; ks++) {
            wgmma_ss_n96_t1(ag, dA0 + k * 1024 + ks * 2, dB0 + s3 * 2048 + ks * 128, (k | ks) != 0);
            wgmma_ss_n96_t1(au, dA0 + k * 1024 + ks * 2, dB0 + s3 * 2048 + 1024 + ks * 128, (k | ks) != 0);
          }
          wg_commit();
          if (k > 0) { wg_wait<1>(); release(prev); }
          prev = s3; s3 = s3 == 6 ? 4 : s3 + 1;
        }
        wg_wait<0>(); pin(ag); pin(au);
        release(prev);
#pragma unroll
        for (int j = 0; j < 24; j++) act[32 + j] = swiglu(ag[2 * j], ag[2 * j + 1], au[2 * j], au[2 * j + 1]);
      }
      pin(act);
      TS(15);
      float acc[128];
#pragma unroll 1
      for (int pass = 0; pass < 2; pass++) {
#pragma unroll
        for (int k = 0; k < 4; k++) {
          mbar_wait(FULL(s3), (pf >> s3) & 1); pf ^= 1u << s3;
          wg_fence();
#pragma unroll
          for (int ks = 0; ks < (k < 3 ? 4 : 2); ks++) wgmma_rs_n256_t1(acc, act[16 * k + 4 * ks], act[16 * k + 4 * ks + 1], act[16 * k + 4 * ks + 2], act[16 * k + 4 * ks + 3], dB0 + s3 * 2048 + ks * 128, (k | ks) != 0);
          wg_commit();
          if (k > 0) { wg_wait<1>(); if (pass == 0 || k == 1) release(prev); }
          prev = s3; s3 = s3 == 6 ? 4 : s3 + 1;
        }
        wg_wait<0>(); pin(acc); pin(act);
        if (pass == 0) release(prev);
        store_part(acc, pass);
      }
    }
    asm volatile("barrier.cluster.arrive.relaxed.aligned;" ::: "memory");
    TS(16);

    {
      uint32_t gb[8];
      {
        unsigned long long pg[8];
#pragma unroll
        for (int j = 0; j < 8; j++) pg[j] = ld_ll(&g_modll[1280 + mcol + 4 * j]);
#pragma unroll
        for (int j = 0; j < 8; j++) gb[j] = get_ll(&g_modll[1280 + mcol + 4 * j], pg[j], tag);
      }
      exchange(2);
      TS(17);
      if (b == 0 && ct == 0) g_epoch = tag;
      float y[32];
      gather(y);
      uint32_t ow[16];
#pragma unroll
      for (int j = 0; j < 8; j++) {
        ow[2 * j] = pack2(fmaf(blo(gb[j]), y[4 * j], blo(x1[2 * j])), fmaf(bhi(gb[j]), y[4 * j + 1], bhi(x1[2 * j])));
        ow[2 * j + 1] = pack2(fmaf(blo(gb[j]), y[4 * j + 2], blo(x1[2 * j + 1])), fmaf(bhi(gb[j]), y[4 * j + 3], bhi(x1[2 * j + 1])));
      }
      write_rows(ow, out);
      if (wid == 0) asm volatile("cp.async.bulk.wait_group.read 0;" ::: "memory");
    }
    TS(18);
    asm volatile("barrier.cluster.wait.aligned;" ::: "memory");
  }
}

typedef CUresult (*EncodeFn)(CUtensorMap*, CUtensorMapDataType, cuuint32_t, void*, const cuuint64_t*, const cuuint64_t*, const cuuint32_t*, const cuuint32_t*,
                             CUtensorMapInterleave, CUtensorMapSwizzle, CUtensorMapL2promotion, CUtensorMapFloatOOBfill);

void make_map(EncodeFn fn, CUtensorMap* m, const void* p, uint64_t rows, uint64_t cols, uint32_t box_rows) {
  cuuint64_t dims[2] = {cols, rows};
  cuuint64_t strides[1] = {cols * 2};
  cuuint32_t box[2] = {64, box_rows};
  cuuint32_t es[2] = {1, 1};
  fn(m, CU_TENSOR_MAP_DATA_TYPE_BFLOAT16, 2, const_cast<void*>(p), dims, strides, box, es, CU_TENSOR_MAP_INTERLEAVE_NONE, CU_TENSOR_MAP_SWIZZLE_128B,
     CU_TENSOR_MAP_L2_PROMOTION_L2_128B, CU_TENSOR_MAP_FLOAT_OOB_FILL_NONE);
}

}

extern "C" void kernel_launch(void* const* d_in, const int* in_sizes, int n_in, void* d_out, int out_size) {
  (void)in_sizes; (void)n_in; (void)out_size;
  typedef const __nv_bfloat16* P;
  P x = (P)d_in[0], k = (P)d_in[1], v = (P)d_in[2], wq = (P)d_in[3], wo = (P)d_in[4];
  P wg = (P)d_in[6], wu = (P)d_in[7], wd = (P)d_in[8], c = (P)d_in[9], wmod = (P)d_in[10];
  static EncodeFn fn = nullptr;
  static void* h2p = nullptr;
  if (!fn) {
    void* p = nullptr;
    cudaDriverEntryPointQueryResult qr;
    cudaGetDriverEntryPoint("cuTensorMapEncodeTiled", &p, cudaEnableDefault, &qr);
    fn = (EncodeFn)p;
    cudaGetSymbolAddress(&h2p, g_h2);
    cudaFuncSetAttribute(fused_kernel, cudaFuncAttributeMaxDynamicSharedMemorySize, SMEM_BYTES);
  }
  Maps mp;
  make_map(fn, &mp.wq, wq, 512, 4096, 64);
  make_map(fn, &mp.k, k, 8 * SEQ, DH, 128);
  make_map(fn, &mp.v, v, 8 * SEQ, DH, 128);
  make_map(fn, &mp.wo, wo, 4096, DM, 64);
  make_map(fn, &mp.wg, wg, DM, FF, 64);
  make_map(fn, &mp.wu, wu, DM, FF, 64);
  make_map(fn, &mp.wd, wd, FF, DM, 64);
  make_map(fn, &mp.h2, h2p, SEQ, DM, 128);
  fused_kernel<<<128, 384, SMEM_BYTES>>>(mp, x, k, wo, wg, wu, wd, c, wmod, (__nv_bfloat16*)d_out);
}
```

```cpp
#include <cuda_runtime.h>
#include <cuda_bf16.h>
#include <cuda.h>
#include <stdint.h>

namespace {

constexpr int SEQ = 2048, DM = 512, DH = 128, FF = 1792, FS = 224;
constexpr int SLOT = 32768, HALF = 16384;
constexpr int OFF_BAR = 7 * SLOT;
constexpr int OFF_MODSM = OFF_BAR + 320;
constexpr int OFF_RED = OFF_MODSM + 2048;
constexpr int OFF_RED2 = OFF_RED + 256;
constexpr int OFF_EPOCH = OFF_RED2 + 192;
constexpr int SMEM_BYTES = 232448;
static_assert(OFF_EPOCH + 16 <= SMEM_BYTES, "smem");

constexpr int CONS_REGS = 232, PROD_REGS = 40;
#define EXP_SPLIT 11

__device__ uint4 g_part[16 * 8 * 8 * 1024];
__device__ __nv_bfloat16 g_h2[SEQ * DM];
struct __align__(128) Sync {
  unsigned long long modll[1536];
  unsigned int flag[3 * 16 * 32];
  unsigned int epoch;
};
__device__ Sync g_sync;

struct Maps { CUtensorMap wq, k, v, wo, wg, wu, wd, h2, x; };

__device__ __forceinline__ uint32_t smem_u32(const void* p) { return (uint32_t)__cvta_generic_to_shared(p); }
__device__ __forceinline__ void mbar_init(uint32_t bar, uint32_t cnt) { asm volatile("mbarrier.init.shared::cta.b64 [%0], %1;" :: "r"(bar), "r"(cnt) : "memory"); }
__device__ __forceinline__ void mbar_expect_tx(uint32_t bar, uint32_t bytes) { asm volatile("mbarrier.arrive.expect_tx.shared::cta.b64 _, [%0], %1;" :: "r"(bar), "r"(bytes) : "memory"); }
__device__ __forceinline__ void mbar_wait(uint32_t bar, uint32_t par) {
  asm volatile(
    "{\n.reg .pred p;\n.reg .u32 n;\n"
    "mbarrier.try_wait.parity.shared::cta.b64 p, [%0], %1;\n"
    "@p bra W_DONE;\n"
    "mov.u32 n, 0;\n"
    "W_LOOP:\n"
    "mbarrier.try_wait.parity.shared::cta.b64 p, [%0], %1;\n"
    "@p bra W_DONE;\n"
    "add.u32 n, n, 1;\n"
    "setp.lt.u32 p, n, 0x1000000;\n"
    "@p bra W_LOOP;\n"
    "trap;\n"
    "W_DONE:\n}" :: "r"(bar), "r"(par) : "memory");
}
__device__ __forceinline__ void tma_load(uint32_t dst, const CUtensorMap* m, uint32_t bar, int c0, int c1) {
  asm volatile("cp.async.bulk.tensor.2d.shared::cluster.global.mbarrier::complete_tx::bytes [%0], [%1, {%3, %4}], [%2];" :: "r"(dst), "l"(m), "r"(bar), "r"(c0), "r"(c1) : "memory");
}
__device__ __forceinline__ void tma_load_mc(uint32_t dst, const CUtensorMap* m, uint32_t bar, int c0, int c1) {
  asm volatile("cp.async.bulk.tensor.2d.shared::cluster.global.mbarrier::complete_tx::bytes.multicast::cluster [%0], [%1, {%3, %4}], [%2], %5;" :: "r"(dst), "l"(m), "r"(bar), "r"(c0), "r"(c1), "h"((uint16_t)3) : "memory");
}
__device__ __forceinline__ void tma_prefetch(const CUtensorMap* m, int c0, int c1) {
  asm volatile("cp.async.bulk.prefetch.tensor.2d.L2.global [%0, {%1, %2}];" :: "l"(m), "r"(c0), "r"(c1) : "memory");
}
__device__ __forceinline__ void bulk_prefetch(const void* p, uint32_t bytes) {
  asm volatile("cp.async.bulk.prefetch.L2.global [%0], %1;" :: "l"(p), "r"(bytes) : "memory");
}
__device__ __forceinline__ void bulk_load(uint32_t dst, const void* src, uint32_t bytes, uint32_t bar) {
  asm volatile("cp.async.bulk.shared::cluster.global.mbarrier::complete_tx::bytes [%0], [%1], %2, [%3];" :: "r"(dst), "l"(src), "r"(bytes), "r"(bar) : "memory");
}
__device__ __forceinline__ void desc_prefetch(const CUtensorMap* m) { asm volatile("prefetch.tensormap [%0];" :: "l"(m) : "memory"); }
__device__ __forceinline__ void fence_async_smem() { asm volatile("fence.proxy.async.shared::cta;" ::: "memory"); }
__device__ __forceinline__ void fence_async_all() { asm volatile("fence.proxy.async;" ::: "memory"); }
__device__ __forceinline__ void fence_gpu() { asm volatile("fence.acq_rel.gpu;" ::: "memory"); }
__device__ __forceinline__ void bar_sync(int id, int n) { asm volatile("bar.sync %0, %1;" :: "r"(id), "r"(n) : "memory"); }
__device__ __forceinline__ void bar_arrive(int id, int n) { asm volatile("bar.arrive %0, %1;" :: "r"(id), "r"(n) : "memory"); }
__device__ __forceinline__ void wg_fence() { asm volatile("wgmma.fence.sync.aligned;" ::: "memory"); }
__device__ __forceinline__ void wg_commit() { asm volatile("wgmma.commit_group.sync.aligned;" ::: "memory"); }
template <int N> __device__ __forceinline__ void wg_wait() { asm volatile("wgmma.wait_group.sync.aligned %0;" :: "n"(N) : "memory"); }
template <int N> __device__ __forceinline__ void pin(float (&r)[N]) {
#pragma unroll
  for (int i = 0; i < N; i++) asm volatile("" : "+f"(r[i]) :: "memory");
}
template <int N> __device__ __forceinline__ void pin(uint32_t (&r)[N]) {
#pragma unroll
  for (int i = 0; i < N; i++) asm volatile("" : "+r"(r[i]) :: "memory");
}
__device__ __forceinline__ uint64_t make_desc(uint32_t addr, uint32_t lbo, uint32_t sbo) {
  return (uint64_t)((addr & 0x3FFFF) >> 4) | ((uint64_t)(lbo >> 4) << 16) | ((uint64_t)(sbo >> 4) << 32) | (1ull << 62);
}
__device__ __forceinline__ float ex2(float x) { float y; asm("ex2.approx.ftz.f32 %0, %1;" : "=f"(y) : "f"(x)); return y; }
__device__ __forceinline__ float tanh_fast(float x) { float y; asm("tanh.approx.f32 %0, %1;" : "=f"(y) : "f"(x)); return y; }
__device__ __forceinline__ uint32_t pack2(float lo, float hi) { uint32_t r; asm("cvt.rn.bf16x2.f32 %0, %1, %2;" : "=r"(r) : "f"(hi), "f"(lo)); return r; }
__device__ __forceinline__ float blo(uint32_t w) { return __uint_as_float(w << 16); }
__device__ __forceinline__ float bhi(uint32_t w) { return __uint_as_float(w & 0xffff0000u); }
__device__ __forceinline__ float bround(float x) { return blo(pack2(x, 0.f)); }
__device__ __forceinline__ uint32_t hfma2(uint32_t a, uint32_t b, uint32_t c) { uint32_t r; asm("fma.rn.bf16x2 %0, %1, %2, %3;" : "=r"(r) : "r"(a), "r"(b), "r"(c)); return r; }
__device__ __forceinline__ uint32_t one_plus(uint32_t w) { return pack2(1.f + blo(w), 1.f + bhi(w)); }
__device__ __forceinline__ void ldsm4(uint32_t addr, uint32_t& a, uint32_t& b, uint32_t& c, uint32_t& d) {
  asm volatile("ldmatrix.sync.aligned.m8n8.x4.shared.b16 {%0,%1,%2,%3}, [%4];" : "=r"(a), "=r"(b), "=r"(c), "=r"(d) : "r"(addr) : "memory");
}
__device__ __forceinline__ void stsm4(uint32_t addr, uint32_t a, uint32_t b, uint32_t c, uint32_t d) {
  asm volatile("stmatrix.sync.aligned.m8n8.x4.shared.b16 [%0], {%1,%2,%3,%4};" :: "r"(addr), "r"(a), "r"(b), "r"(c), "r"(d) : "memory");
}
__device__ __forceinline__ void sts128(uint32_t addr, uint32_t a, uint32_t b, uint32_t c, uint32_t d) {
  asm volatile("st.shared.v4.b32 [%0], {%1,%2,%3,%4};" :: "r"(addr), "r"(a), "r"(b), "r"(c), "r"(d) : "memory");
}
__device__ __forceinline__ uint4 lds128(uint32_t addr) {
  uint4 v; asm volatile("ld.shared.v4.b32 {%0,%1,%2,%3}, [%4];" : "=r"(v.x), "=r"(v.y), "=r"(v.z), "=r"(v.w) : "r"(addr) : "memory"); return v;
}
__device__ __forceinline__ void sts32(uint32_t addr, uint32_t v) { asm volatile("st.shared.b32 [%0], %1;" :: "r"(addr), "r"(v) : "memory"); }
__device__ __forceinline__ uint32_t lds32(uint32_t addr) { uint32_t v; asm volatile("ld.shared.b32 %0, [%1];" : "=r"(v) : "r"(addr) : "memory"); return v; }
__device__ __forceinline__ uint4 ldg_nc128(const void* p) {
  uint4 v; asm volatile("ld.global.nc.v4.b32 {%0,%1,%2,%3}, [%4];" : "=r"(v.x), "=r"(v.y), "=r"(v.z), "=r"(v.w) : "l"(p)); return v;
}
__device__ __forceinline__ uint32_t ldg_nc32(const void* p) { uint32_t v; asm volatile("ld.global.nc.b32 %0, [%1];" : "=r"(v) : "l"(p)); return v; }
__device__ __forceinline__ void stg128(void* p, uint32_t a, uint32_t b, uint32_t c, uint32_t d) {
  asm volatile("st.global.v4.b32 [%0], {%1,%2,%3,%4};" :: "l"(p), "r"(a), "r"(b), "r"(c), "r"(d) : "memory");
}
__device__ __forceinline__ unsigned long long ld_ll(const unsigned long long* p) {
  unsigned long long v; asm volatile("ld.relaxed.gpu.global.b64 %0, [%1];" : "=l"(v) : "l"(p) : "memory"); return v;
}
__device__ __forceinline__ void st_ll(unsigned long long* p, uint32_t val, uint32_t tag) {
  asm volatile("st.relaxed.gpu.global.b64 [%0], %1;" :: "l"(p), "l"(((unsigned long long)tag << 32) | val) : "memory");
}
__device__ __forceinline__ uint32_t get_ll(const unsigned long long* p, unsigned long long v, uint32_t tag) {
  uint32_t r;
  asm volatile(
    "{\n.reg .pred p;\n.reg .u32 n, t;\n.reg .b64 v;\n"
    "mov.b64 {%0, t}, %2;\n"
    "setp.eq.u32 p, t, %3;\n"
    "@p bra L_DONE;\n"
    "mov.u32 n, 0;\n"
    "L_LOOP:\n"
    "ld.relaxed.gpu.global.b64 v, [%1];\n"
    "mov.b64 {%0, t}, v;\n"
    "setp.eq.u32 p, t, %3;\n"
    "@p bra L_DONE;\n"
    "add.u32 n, n, 1;\n"
    "setp.lt.u32 p, n, 0x1000000;\n"
    "@p bra L_LOOP;\n"
    "trap;\n"
    "L_DONE:\n}" : "=&r"(r) : "l"(p), "l"(v), "r"(tag) : "memory");
  return r;
}
__device__ __forceinline__ void flag_set(unsigned int* f, uint32_t tag) { asm volatile("st.release.gpu.global.u32 [%0], %1;" :: "l"(f), "r"(tag) : "memory"); }
__device__ __forceinline__ uint32_t flag_get(const unsigned int* f) { uint32_t v; asm volatile("ld.relaxed.gpu.global.u32 %0, [%1];" : "=r"(v) : "l"(f) : "memory"); return v; }
__device__ __forceinline__ void trap_if(bool c) { asm volatile("{\n.reg .pred p;\nsetp.ne.u32 p, %0, 0;\n@p trap;\n}" :: "r"((uint32_t)c)); }
__device__ __forceinline__ float silu_bf(float x) { return bround(x / (1.f + __expf(-x))); }
__device__ __forceinline__ void mma16816(float& c0, float& c1, float& c2, float& c3, uint32_t a0, uint32_t a1, uint32_t a2, uint32_t a3, uint32_t b0, uint32_t b1) {
  asm("mma.sync.aligned.m16n8k16.row.col.f32.bf16.bf16.f32 {%0,%1,%2,%3}, {%4,%5,%6,%7}, {%8,%9}, {%0,%1,%2,%3};"
      : "+f"(c0), "+f"(c1), "+f"(c2), "+f"(c3) : "r"(a0), "r"(a1), "r"(a2), "r"(a3), "r"(b0), "r"(b1));
}

template <int O, int N> __device__ __forceinline__ void xreduce(float (&v)[N], int lane) {
  const bool up = lane & O;
#pragma unroll
  for (int i = 0; i < O; i++) { const float snd = up ? v[i] : v[i + O], kp = up ? v[i + O] : v[i]; v[i] = kp + __shfl_xor_sync(~0u, snd, O); }
}

template <int N> struct IC { __device__ constexpr operator int() const { return N; } };

__device__ __forceinline__ void wgmma_rs_n128_t0(float (&d)[64], uint32_t a0, uint32_t a1, uint32_t a2, uint32_t a3, uint64_t db, int scale_d) {
  asm volatile(
    "{\n.reg .pred p;\nsetp.ne.b32 p, %69, 0;\n"
    "wgmma.mma_async.sync.aligned.m64n128k16.f32.bf16.bf16 {"
    "%0, %1, %2, %3, %4, %5, %6, %7, %8, %9, %10, %11, %12, %13, %14, %15, "
    "%16, %17, %18, %19, %20, %21, %22, %23, %24, %25, %26, %27, %28, %29, %30, %31, "
    "%32, %33, %34, %35, %36, %37, %38, %39, %40, %41, %42, %43, %44, %45, %46, %47, "
    "%48, %49, %50, %51, %52, %53, %54, %55, %56, %57, %58, %59, %60, %61, %62, %63"
    "}, {%64, %65, %66, %67}, %68, p, 1, 1, 0;\n}\n"
    : "+f"(d[0]), "+f"(d[1]), "+f"(d[2]), "+f"(d[3]), "+f"(d[4]), "+f"(d[5]), "+f"(d[6]), "+f"(d[7]),
      "+f"(d[8]), "+f"(d[9]), "+f"(d[10]), "+f"(d[11]), "+f"(d[12]), "+f"(d[13]), "+f"(d[14]), "+f"(d[15]),
      "+f"(d[16]), "+f"(d[17]), "+f"(d[18]), "+f"(d[19]), "+f"(d[20]), "+f"(d[21]), "+f"(d[22]), "+f"(d[23]),
      "+f"(d[24]), "+f"(d[25]), "+f"(d[26]), "+f"(d[27]), "+f"(d[28]), "+f"(d[29]), "+f"(d[30]), "+f"(d[31]),
      "+f"(d[32]), "+f"(d[33]), "+f"(d[34]), "+f"(d[35]), "+f"(d[36]), "+f"(d[37]), "+f"(d[38]), "+f"(d[39]),
      "+f"(d[40]), "+f"(d[41]), "+f"(d[42]), "+f"(d[43]), "+f"(d[44]), "+f"(d[45]), "+f"(d[46]), "+f"(d[47]),
      "+f"(d[48]), "+f"(d[49]), "+f"(d[50]), "+f"(d[51]), "+f"(d[52]), "+f"(d[53]), "+f"(d[54]), "+f"(d[55]),
      "+f"(d[56]), "+f"(d[57]), "+f"(d[58]), "+f"(d[59]), "+f"(d[60]), "+f"(d[61]), "+f"(d[62]), "+f"(d[63])
    : "r"(a0), "r"(a1), "r"(a2), "r"(a3), "l"(db), "r"(scale_d));
}
__device__ __forceinline__ void wgmma_rs_n128_t1(float (&d)[64], uint32_t a0, uint32_t a1, uint32_t a2, uint32_t a3, uint64_t db, int scale_d) {
  asm volatile(
    "{\n.reg .pred p;\nsetp.ne.b32 p, %69, 0;\n"
    "wgmma.mma_async.sync.aligned.m64n128k16.f32.bf16.bf16 {"
    "%0, %1, %2, %3, %4, %5, %6, %7, %8, %9, %10, %11, %12, %13, %14, %15, "
    "%16, %17, %18, %19, %20, %21, %22, %23, %24, %25, %26, %27, %28, %29, %30, %31, "
    "%32, %33, %34, %35, %36, %37, %38, %39, %40, %41, %42, %43, %44, %45, %46, %47, "
    "%48, %49, %50, %51, %52, %53, %54, %55, %56, %57, %58, %59, %60, %61, %62, %63"
    "}, {%64, %65, %66, %67}, %68, p, 1, 1, 1;\n}\n"
    : "+f"(d[0]), "+f"(d[1]), "+f"(d[2]), "+f"(d[3]), "+f"(d[4]), "+f"(d[5]), "+f"(d[6]), "+f"(d[7]),
      "+f"(d[8]), "+f"(d[9]), "+f"(d[10]), "+f"(d[11]), "+f"(d[12]), "+f"(d[13]), "+f"(d[14]), "+f"(d[15]),
      "+f"(d[16]), "+f"(d[17]), "+f"(d[18]), "+f"(d[19]), "+f"(d[20]), "+f"(d[21]), "+f"(d[22]), "+f"(d[23]),
      "+f"(d[24]), "+f"(d[25]), "+f"(d[26]), "+f"(d[27]), "+f"(d[28]), "+f"(d[29]), "+f"(d[30]), "+f"(d[31]),
      "+f"(d[32]), "+f"(d[33]), "+f"(d[34]), "+f"(d[35]), "+f"(d[36]), "+f"(d[37]), "+f"(d[38]), "+f"(d[39]),
      "+f"(d[40]), "+f"(d[41]), "+f"(d[42]), "+f"(d[43]), "+f"(d[44]), "+f"(d[45]), "+f"(d[46]), "+f"(d[47]),
      "+f"(d[48]), "+f"(d[49]), "+f"(d[50]), "+f"(d[51]), "+f"(d[52]), "+f"(d[53]), "+f"(d[54]), "+f"(d[55]),
      "+f"(d[56]), "+f"(d[57]), "+f"(d[58]), "+f"(d[59]), "+f"(d[60]), "+f"(d[61]), "+f"(d[62]), "+f"(d[63])
    : "r"(a0), "r"(a1), "r"(a2), "r"(a3), "l"(db), "r"(scale_d));
}
__device__ __forceinline__ void wgmma_ss_n256_t1(float (&d)[128], uint64_t da, uint64_t db, int scale_d) {
  asm volatile(
    "{\n.reg .pred p;\nsetp.ne.b32 p, %130, 0;\n"
    "wgmma.mma_async.sync.aligned.m64n256k16.f32.bf16.bf16 {"
    "%0, %1, %2, %3, %4, %5, %6, %7, %8, %9, %10, %11, %12, %13, %14, %15, "
    "%16, %17, %18, %19, %20, %21, %22, %23, %24, %25, %26, %27, %28, %29, %30, %31, "
    "%32, %33, %34, %35, %36, %37, %38, %39, %40, %41, %42, %43, %44, %45, %46, %47, "
    "%48, %49, %50, %51, %52, %53, %54, %55, %56, %57, %58, %59, %60, %61, %62, %63, "
    "%64, %65, %66, %67, %68, %69, %70, %71, %72, %73, %74, %75, %76, %77, %78, %79, "
    "%80, %81, %82, %83, %84, %85, %86, %87, %88, %89, %90, %91, %92, %93, %94, %95, "
    "%96, %97, %98, %99, %100, %101, %102, %103, %104, %105, %106, %107, %108, %109, %110, %111, "
    "%112, %113, %114, %115, %116, %117, %118, %119, %120, %121, %122, %123, %124, %125, %126, %127"
    "}, %128, %129, p, 1, 1, 0, 1;\n}\n"
    : "+f"(d[0]), "+f"(d[1]), "+f"(d[2]), "+f"(d[3]), "+f"(d[4]), "+f"(d[5]), "+f"(d[6]), "+f"(d[7]),
      "+f"(d[8]), "+f"(d[9]), "+f"(d[10]), "+f"(d[11]), "+f"(d[12]), "+f"(d[13]), "+f"(d[14]), "+f"(d[15]),
      "+f"(d[16]), "+f"(d[17]), "+f"(d[18]), "+f"(d[19]), "+f"(d[20]), "+f"(d[21]), "+f"(d[22]), "+f"(d[23]),
      "+f"(d[24]), "+f"(d[25]), "+f"(d[26]), "+f"(d[27]), "+f"(d[28]), "+f"(d[29]), "+f"(d[30]), "+f"(d[31]),
      "+f"(d[32]), "+f"(d[33]), "+f"(d[34]), "+f"(d[35]), "+f"(d[36]), "+f"(d[37]), "+f"(d[38]), "+f"(d[39]),
      "+f"(d[40]), "+f"(d[41]), "+f"(d[42]), "+f"(d[43]), "+f"(d[44]), "+f"(d[45]), "+f"(d[46]), "+f"(d[47]),
      "+f"(d[48]), "+f"(d[49]), "+f"(d[50]), "+f"(d[51]), "+f"(d[52]), "+f"(d[53]), "+f"(d[54]), "+f"(d[55]),
      "+f"(d[56]), "+f"(d[57]), "+f"(d[58]), "+f"(d[59]), "+f"(d[60]), "+f"(d[61]), "+f"(d[62]), "+f"(d[63]),
      "+f"(d[64]), "+f"(d[65]), "+f"(d[66]), "+f"(d[67]), "+f"(d[68]), "+f"(d[69]), "+f"(d[70]), "+f"(d[71]),
      "+f"(d[72]), "+f"(d[73]), "+f"(d[74]), "+f"(d[75]), "+f"(d[76]), "+f"(d[77]), "+f"(d[78]), "+f"(d[79]),
      "+f"(d[80]), "+f"(d[81]), "+f"(d[82]), "+f"(d[83]), "+f"(d[84]), "+f"(d[85]), "+f"(d[86]), "+f"(d[87]),
      "+f"(d[88]), "+f"(d[89]), "+f"(d[90]), "+f"(d[91]), "+f"(d[92]), "+f"(d[93]), "+f"(d[94]), "+f"(d[95]),
      "+f"(d[96]), "+f"(d[97]), "+f"(d[98]), "+f"(d[99]), "+f"(d[100]), "+f"(d[101]), "+f"(d[102]), "+f"(d[103]),
      "+f"(d[104]), "+f"(d[105]), "+f"(d[106]), "+f"(d[107]), "+f"(d[108]), "+f"(d[109]), "+f"(d[110]), "+f"(d[111]),
      "+f"(d[112]), "+f"(d[113]), "+f"(d[114]), "+f"(d[115]), "+f"(d[116]), "+f"(d[117]), "+f"(d[118]), "+f"(d[119]),
      "+f"(d[120]), "+f"(d[121]), "+f"(d[122]), "+f"(d[123]), "+f"(d[124]), "+f"(d[125]), "+f"(d[126]), "+f"(d[127])
    : "l"(da), "l"(db), "r"(scale_d));
}
__device__ __forceinline__ void wgmma_rs_n256_t1(float (&d)[128], uint32_t a0, uint32_t a1, uint32_t a2, uint32_t a3, uint64_t db, int scale_d) {
  asm volatile(
    "{\n.reg .pred p;\nsetp.ne.b32 p, %133, 0;\n"
    "wgmma.mma_async.sync.aligned.m64n256k16.f32.bf16.bf16 {"
    "%0, %1, %2, %3, %4, %5, %6, %7, %8, %9, %10, %11, %12, %13, %14, %15, "
    "%16, %17, %18, %19, %20, %21, %22, %23, %24, %25, %26, %27, %28, %29, %30, %31, "
    "%32, %33, %34, %35, %36, %37, %38, %39, %40, %41, %42, %43, %44, %45, %46, %47, "
    "%48, %49, %50, %51, %52, %53, %54, %55, %56, %57, %58, %59, %60, %61, %62, %63, "
    "%64, %65, %66, %67, %68, %69, %70, %71, %72, %73, %74, %75, %76, %77, %78, %79, "
    "%80, %81, %82, %83, %84, %85, %86, %87, %88, %89, %90, %91, %92, %93, %94, %95, "
    "%96, %97, %98, %99, %100, %101, %102, %103, %104, %105, %106, %107, %108, %109, %110, %111, "
    "%112, %113, %114, %115, %116, %117, %118, %119, %120, %121, %122, %123, %124, %125, %126, %127"
    "}, {%128, %129, %130, %131}, %132, p, 1, 1, 1;\n}\n"
    : "+f"(d[0]), "+f"(d[1]), "+f"(d[2]), "+f"(d[3]), "+f"(d[4]), "+f"(d[5]), "+f"(d[6]), "+f"(d[7]),
      "+f"(d[8]), "+f"(d[9]), "+f"(d[10]), "+f"(d[11]), "+f"(d[12]), "+f"(d[13]), "+f"(d[14]), "+f"(d[15]),
      "+f"(d[16]), "+f"(d[17]), "+f"(d[18]), "+f"(d[19]), "+f"(d[20]), "+f"(d[21]), "+f"(d[22]), "+f"(d[23]),
      "+f"(d[24]), "+f"(d[25]), "+f"(d[26]), "+f"(d[27]), "+f"(d[28]), "+f"(d[29]), "+f"(d[30]), "+f"(d[31]),
      "+f"(d[32]), "+f"(d[33]), "+f"(d[34]), "+f"(d[35]), "+f"(d[36]), "+f"(d[37]), "+f"(d[38]), "+f"(d[39]),
      "+f"(d[40]), "+f"(d[41]), "+f"(d[42]), "+f"(d[43]), "+f"(d[44]), "+f"(d[45]), "+f"(d[46]), "+f"(d[47]),
      "+f"(d[48]), "+f"(d[49]), "+f"(d[50]), "+f"(d[51]), "+f"(d[52]), "+f"(d[53]), "+f"(d[54]), "+f"(d[55]),
      "+f"(d[56]), "+f"(d[57]), "+f"(d[58]), "+f"(d[59]), "+f"(d[60]), "+f"(d[61]), "+f"(d[62]), "+f"(d[63]),
      "+f"(d[64]), "+f"(d[65]), "+f"(d[66]), "+f"(d[67]), "+f"(d[68]), "+f"(d[69]), "+f"(d[70]), "+f"(d[71]),
      "+f"(d[72]), "+f"(d[73]), "+f"(d[74]), "+f"(d[75]), "+f"(d[76]), "+f"(d[77]), "+f"(d[78]), "+f"(d[79]),
      "+f"(d[80]), "+f"(d[81]), "+f"(d[82]), "+f"(d[83]), "+f"(d[84]), "+f"(d[85]), "+f"(d[86]), "+f"(d[87]),
      "+f"(d[88]), "+f"(d[89]), "+f"(d[90]), "+f"(d[91]), "+f"(d[92]), "+f"(d[93]), "+f"(d[94]), "+f"(d[95]),
      "+f"(d[96]), "+f"(d[97]), "+f"(d[98]), "+f"(d[99]), "+f"(d[100]), "+f"(d[101]), "+f"(d[102]), "+f"(d[103]),
      "+f"(d[104]), "+f"(d[105]), "+f"(d[106]), "+f"(d[107]), "+f"(d[108]), "+f"(d[109]), "+f"(d[110]), "+f"(d[111]),
      "+f"(d[112]), "+f"(d[113]), "+f"(d[114]), "+f"(d[115]), "+f"(d[116]), "+f"(d[117]), "+f"(d[118]), "+f"(d[119]),
      "+f"(d[120]), "+f"(d[121]), "+f"(d[122]), "+f"(d[123]), "+f"(d[124]), "+f"(d[125]), "+f"(d[126]), "+f"(d[127])
    : "r"(a0), "r"(a1), "r"(a2), "r"(a3), "l"(db), "r"(scale_d));
}
__device__ __forceinline__ void wgmma_ss_n96_t1(float (&d)[48], uint64_t da, uint64_t db, int scale_d) {
  asm volatile(
    "{\n.reg .pred p;\nsetp.ne.b32 p, %50, 0;\n"
    "wgmma.mma_async.sync.aligned.m64n96k16.f32.bf16.bf16 {"
    "%0, %1, %2, %3, %4, %5, %6, %7, %8, %9, %10, %11, %12, %13, %14, %15, "
    "%16, %17, %18, %19, %20, %21, %22, %23, %24, %25, %26, %27, %28, %29, %30, %31, "
    "%32, %33, %34, %35, %36, %37, %38, %39, %40, %41, %42, %43, %44, %45, %46, %47"
    "}, %48, %49, p, 1, 1, 0, 1;\n}\n"
    : "+f"(d[0]), "+f"(d[1]), "+f"(d[2]), "+f"(d[3]), "+f"(d[4]), "+f"(d[5]), "+f"(d[6]), "+f"(d[7]),
      "+f"(d[8]), "+f"(d[9]), "+f"(d[10]), "+f"(d[11]), "+f"(d[12]), "+f"(d[13]), "+f"(d[14]), "+f"(d[15]),
      "+f"(d[16]), "+f"(d[17]), "+f"(d[18]), "+f"(d[19]), "+f"(d[20]), "+f"(d[21]), "+f"(d[22]), "+f"(d[23]),
      "+f"(d[24]), "+f"(d[25]), "+f"(d[26]), "+f"(d[27]), "+f"(d[28]), "+f"(d[29]), "+f"(d[30]), "+f"(d[31]),
      "+f"(d[32]), "+f"(d[33]), "+f"(d[34]), "+f"(d[35]), "+f"(d[36]), "+f"(d[37]), "+f"(d[38]), "+f"(d[39]),
      "+f"(d[40]), "+f"(d[41]), "+f"(d[42]), "+f"(d[43]), "+f"(d[44]), "+f"(d[45]), "+f"(d[46]), "+f"(d[47])
    : "l"(da), "l"(db), "r"(scale_d));
}

#define TS(k)

constexpr int B_PP = 1;
constexpr int B_CONS = 3;
constexpr int B_WG = 4;
constexpr int B_AUX = 6;
constexpr int B_X = 7;

__global__ void __cluster_dims__(2, 1, 1) __launch_bounds__(384, 1)
fused_kernel(const __grid_constant__ Maps mp, const __nv_bfloat16* __restrict__ x, const __nv_bfloat16* __restrict__ kc,
             const __nv_bfloat16* __restrict__ wo, const __nv_bfloat16* __restrict__ wg, const __nv_bfloat16* __restrict__ wu,
             const __nv_bfloat16* __restrict__ wd, const __nv_bfloat16* __restrict__ cvec, const __nv_bfloat16* __restrict__ wmod,
             __nv_bfloat16* __restrict__ out) {
  extern __shared__ __align__(1024) uint8_t sm_raw[];
  const uint32_t sb = smem_u32(sm_raw);
  const int tid = threadIdx.x, lane = tid & 31;
  const int b = blockIdx.x;
  const uint32_t rank = b & 1;
  const int g = (b >> 1) & 7;
  const int rt = (b >> 4) * 2 + rank;
  auto FULL = [&](int h) { return sb + OFF_BAR + 8 * h; };
  auto EMPTY = [&](int h) { return sb + OFF_BAR + 112 + 8 * h; };
  auto AFULL = [&](int s) { return sb + OFF_BAR + 200 + 8 * s; };
  auto AEMPTY = [&](int s) { return sb + OFF_BAR + 232 + 8 * s; };
  auto XFULL = [&](int r) { return sb + OFF_BAR + 288 + 8 * r; };

  if (tid < 32) {
    if (tid == 0) {
      trap_if(sb & 1023);
      for (int h = 0; h < 14; h++) { mbar_init(FULL(h), 1); mbar_init(EMPTY(h), 16); }
      for (int s = 3; s < 7; s++) { mbar_init(AFULL(s), 1); mbar_init(AEMPTY(s), 16); mbar_init(XFULL(s - 3), 1); }
      asm volatile("fence.mbarrier_init.release.cluster;" ::: "memory");
      fence_async_smem();
      for (int r = 0; r < 4; r++) mbar_expect_tx(XFULL(r), SLOT);
    }
    __syncwarp();
    tma_load(sb + (lane & 7) * HALF + (lane >> 3) * 4096, &mp.x, XFULL(lane >> 3), (lane & 7) * 64, rt * 128 + (lane >> 3) * 32);
  }
  asm volatile("barrier.cluster.arrive.relaxed.aligned;" ::: "memory");

  if (tid < 128) {
    asm volatile("setmaxnreg.dec.sync.aligned.u32 %0;" :: "n"(PROD_REGS));
    asm volatile("barrier.cluster.wait.aligned;" ::: "memory");
    if (tid == 0) {
      uint32_t pe = 0x3f00;
      auto wait_empty = [&](int h) { mbar_wait(EMPTY(h), (pe >> h) & 1); pe ^= 1u << h; };
      auto load_w = [&](int h, const CUtensorMap* m, int xx, int yy) {
        mbar_expect_tx(FULL(h), HALF);
        tma_load_mc(sb + h * HALF + rank * 8192, m, FULL(h), xx, yy);
        tma_load_mc(sb + h * HALF + rank * 8192 + 4096, m, FULL(h), xx + 64, yy);
      };
      int h6 = 8;
      for (int i = 0; i < 32; i++) {
        wait_empty(h6);
        load_w(h6, &mp.wq, g * 512 + (i < 16 ? 256 : 0) + rank * 128, (i & 15) * 32);
        h6 = h6 == 13 ? 8 : h6 + 1;
        if (i == 5) {
          for (int j = 0; j < 8; j++) tma_prefetch(&mp.wq, g * 512 + (rt < 8 ? 256 : 0) + (j & 3) * 64, (rt & 7) * 64 + (j >> 2) * 32);
          desc_prefetch(&mp.k); desc_prefetch(&mp.v);
        }
        if (i == 6) {
          tma_prefetch(&mp.k, 0, g * SEQ + rt * 128); tma_prefetch(&mp.k, 64, g * SEQ + rt * 128);
          tma_prefetch(&mp.v, 0, g * SEQ + rt * 128); tma_prefetch(&mp.v, 64, g * SEQ + rt * 128);
        }
      }
      auto load_kv = [&](int s, int t, const CUtensorMap* m) {
        if (t < 2) { wait_empty(2 * s); wait_empty(2 * s + 1); } else mbar_wait(AEMPTY(s), ((t >> 1) & 1) ^ 1);
        mbar_expect_tx(AFULL(s), SLOT);
        tma_load_mc(sb + s * SLOT + rank * HALF, m, AFULL(s), rank * 64, g * SEQ + (t & 15) * 128);
      };
      for (int t = 0; t <= 64; t++) {
        if (t < 64) load_kv(5 + (t & 1), t, &mp.k);
        if (t > 0) load_kv(3 + (t & 1), t - 1, &mp.v);
      }
      for (int i = 0; i < 32; i++) {
        const int h = (0x7698dcba >> ((i & 7) * 4)) & 15;
        if (i >= 8) wait_empty(h); else if ((i & 1) == 0) mbar_wait(AEMPTY(h >> 1), 1);
        load_w(h, &mp.wo, (i >> 4) * 256 + rank * 128, g * 512 + (i & 15) * 32);
      }
      auto load_wd = [&](int j, int h) { wait_empty(h); load_w(h, &mp.wd, (j >= 7 ? 256 : 0) + rank * 128, g * FS + (j >= 7 ? j - 7 : j) * 32); };
      h6 = 10;
      for (int i = 0; i < 32; i++) {
        wait_empty(h6);
        load_w(h6, rank ? &mp.wu : &mp.wg, g * FS + (i >> 4) * 128, (i & 15) * 32);
        h6 = h6 == 13 ? 8 : h6 + 1;
        if (i >= 23 && (i & 1)) load_wd((i - 23) >> 1, (i - 23) >> 1);
      }
      for (int j = 5; j < 8; j++) load_wd(j, j);
      for (int j = 8; j < 14; j++) { load_wd(j, h6); h6 = h6 == 13 ? 8 : h6 + 1; }
    } else if (tid >= 32) {
      const int j = tid - 32;
      mbar_wait(AFULL(3), 0);
      if (j == 0) {
        bulk_prefetch((const uint8_t*)wo + (size_t)b * 32768, 32768);
        bulk_prefetch((const uint8_t*)wg + (size_t)b * 14336, 14336);
        bulk_prefetch((const uint8_t*)wu + (size_t)b * 14336, 14336);
        bulk_prefetch((const uint8_t*)wd + (size_t)b * 14336, 14336);
      }
      float a[8];
#pragma unroll
      for (int i = 0; i < 8; i++) a[i] = 0.f;
#pragma unroll 2
      for (int k = j >> 1; k < 512; k += 48) {
        const uint4 w = ldg_nc128(wmod + (size_t)k * 3072 + 1024 + b * 16 + (j & 1) * 8);
        const float sc = silu_bf(__bfloat162float(cvec[k]));
        a[0] += sc * blo(w.x); a[1] += sc * bhi(w.x); a[2] += sc * blo(w.y); a[3] += sc * bhi(w.y);
        a[4] += sc * blo(w.z); a[5] += sc * bhi(w.z); a[6] += sc * blo(w.w); a[7] += sc * bhi(w.w);
      }
#pragma unroll
      for (int i = 0; i < 8; i++) {
#pragma unroll
        for (int o = 2; o < 32; o <<= 1) a[i] += __shfl_xor_sync(~0u, a[i], o);
      }
      if (lane < 2) {
#pragma unroll
        for (int i = 0; i < 8; i++) sts32(sb + OFF_RED2 + ((j >> 5) * 16 + lane * 8 + i) * 4, __float_as_uint(a[i]));
      }
      bar_sync(B_AUX, 96);
      if (j < 8) {
        float v0 = 0.f, v1 = 0.f;
#pragma unroll
        for (int w = 0; w < 3; w++) { v0 += __uint_as_float(lds32(sb + OFF_RED2 + (w * 16 + 2 * j) * 4)); v1 += __uint_as_float(lds32(sb + OFF_RED2 + (w * 16 + 2 * j + 1) * 4)); }
        st_ll(&g_sync.modll[512 + b * 8 + j], pack2(v0, v1), lds32(sb + OFF_EPOCH));
      }
      if (j < 32) {
        const uint32_t tag = lds32(sb + OFF_EPOCH);
#pragma unroll 1
        for (int phase = 0; phase < 3; phase++) {
          bar_sync(B_X, 288);
          if (lane < 8) mbar_expect_tx(FULL(lane), HALF);
          __syncwarp();
          bool done = lane >= 8;
          int n = 0;
          while (!__all_sync(~0u, done)) {
            if (!done && flag_get(&g_sync.flag[(phase * 16 + rt) * 32 + lane]) == tag) {
              fence_gpu();
              fence_async_all();
              if (phase == 1) {
                for (int k = 0; k < 8; k++) tma_load(sb + k * HALF + lane * 2048, &mp.h2, FULL(k), k * 64, rt * 128 + lane * 16);
              } else {
                bulk_load(sb + lane * HALF, g_part + ((size_t)(rt * 8 + g) * 8 + lane) * 1024, HALF, FULL(lane));
              }
              done = true;
            }
            trap_if(++n > (1 << 24));
          }
        }
      }
    }
  } else {
    asm volatile("setmaxnreg.inc.sync.aligned.u32 %0;" :: "n"(CONS_REGS));
    const int ct = tid - 128, cw = ct >> 7, wid = ct >> 5;
    uint32_t rel0;
    asm volatile("mapa.shared::cluster.u32 %0, %1, %2;" : "=r"(rel0) : "r"(EMPTY(0)), "r"(lane & 1));
    auto release = [&](int h) { if (lane < 2) asm volatile("mbarrier.arrive.shared::cluster.b64 _, [%0];" :: "r"(rel0 + 8 * h) : "memory"); };
    auto release_a = [&](int s) { release(15 + s); };
    uint32_t pf = 0;
    auto wait_full = [&](int h) { mbar_wait(FULL(h), (pf >> h) & 1); pf ^= 1u << h; };
    const uint32_t frag_row = wid * 16 + (lane & 15);
    auto frag_addr = [&](int slot, int kk) { return sb + slot * SLOT + (kk >> 2) * 16384 + frag_row * 128 + ((((kk & 3) * 2 + (lane >> 4)) ^ (lane & 7)) << 4); };
    uint32_t tag;
    TS(31);

    {
      asm volatile("ld.relaxed.gpu.global.u32 %0, [%1];" : "=r"(tag) : "l"(&g_sync.epoch) : "memory");
      const uint4 w0 = ldg_nc128(wmod + (size_t)ct * 3072 + b * 8), w1 = ldg_nc128(wmod + (size_t)(ct + 256) * 3072 + b * 8);
      const float c0 = __bfloat162float(cvec[ct]), c1 = __bfloat162float(cvec[ct + 256]);
      asm volatile("barrier.cluster.wait.aligned;" ::: "memory");
      tag += 1;
      if (ct == 0) sts32(sb + OFF_EPOCH, tag);
      {
        const float s0 = silu_bf(c0), s1 = silu_bf(c1);
        float a[8] = {s0 * blo(w0.x) + s1 * blo(w1.x), s0 * bhi(w0.x) + s1 * bhi(w1.x), s0 * blo(w0.y) + s1 * blo(w1.y), s0 * bhi(w0.y) + s1 * bhi(w1.y),
                      s0 * blo(w0.z) + s1 * blo(w1.z), s0 * bhi(w0.z) + s1 * bhi(w1.z), s0 * blo(w0.w) + s1 * blo(w1.w), s0 * bhi(w0.w) + s1 * bhi(w1.w)};
#pragma unroll
        for (int i = 0; i < 4; i++) { const bool up = lane & 16; const float snd = up ? a[i] : a[i + 4], kp = up ? a[i + 4] : a[i]; a[i] = kp + __shfl_xor_sync(~0u, snd, 16); }
#pragma unroll
        for (int i = 0; i < 2; i++) { const bool up = lane & 8; const float snd = up ? a[i] : a[i + 2], kp = up ? a[i + 2] : a[i]; a[i] = kp + __shfl_xor_sync(~0u, snd, 8); }
        { const bool up = lane & 4; const float snd = up ? a[0] : a[1], kp = up ? a[1] : a[0]; a[0] = kp + __shfl_xor_sync(~0u, snd, 4); }
        a[0] += __shfl_xor_sync(~0u, a[0], 2); a[0] += __shfl_xor_sync(~0u, a[0], 1);
        if ((lane & 3) == 0) sts32(sb + OFF_RED + (wid * 8 + (lane >> 2)) * 4, __float_as_uint(a[0]));
        bar_sync(B_CONS, 256);
        if (ct < 4) {
          float v0 = 0.f, v1 = 0.f;
#pragma unroll
          for (int w = 0; w < 8; w++) { v0 += __uint_as_float(lds32(sb + OFF_RED + (w * 8 + 2 * ct) * 4)); v1 += __uint_as_float(lds32(sb + OFF_RED + (w * 8 + 2 * ct + 1) * 4)); }
          st_ll(&g_sync.modll[b * 4 + ct], pack2(v0, v1), tag);
        }
      }
      TS(0);
      uint32_t xr[128];
      const uint32_t xad = sb + (lane >> 3) * HALF + wid * 2048;
      mbar_wait(XFULL(wid >> 1), 0);
      TS(19);
#pragma unroll
      for (int i = 0; i < 16; i++) {
        const uint32_t ad = xad + i * 128 + (((lane & 7) ^ (i & 7)) << 4);
        const uint4 u = lds128(ad), v = lds128(ad + 65536);
        xr[8 * i] = u.x; xr[8 * i + 1] = u.y; xr[8 * i + 2] = u.z; xr[8 * i + 3] = u.w;
        xr[8 * i + 4] = v.x; xr[8 * i + 5] = v.y; xr[8 * i + 6] = v.z; xr[8 * i + 7] = v.w;
      }
      float v[32];
#pragma unroll
      for (int i = 0; i < 16; i++) {
        float s = 0.f, q = 0.f;
#pragma unroll
        for (int j = 0; j < 8; j++) { const float lo = blo(xr[8 * i + j]), hi = bhi(xr[8 * i + j]); s += lo; s += hi; q = fmaf(lo, lo, q); q = fmaf(hi, hi, q); }
        v[2 * i] = s; v[2 * i + 1] = q;
      }
      xreduce<16>(v, lane); xreduce<8>(v, lane); xreduce<4>(v, lane); xreduce<2>(v, lane); xreduce<1>(v, lane);
      float rs, nm;
      {
        const float oth = __shfl_xor_sync(~0u, v[0], 1);
        const float mean = ((lane & 1) ? oth : v[0]) * (1.f / DM), ex = ((lane & 1) ? v[0] : oth) * (1.f / DM);
        const float var = fmaxf(ex - mean * mean, 0.f);
        rs = 1.f / bround(sqrtf(bround(bround(var) + 1e-5f)));
        nm = -bround(mean) * rs;
      }
#pragma unroll
      for (int i = 0; i < 16; i++) {
        const float r = __shfl_sync(~0u, rs, 2 * i), m = __shfl_sync(~0u, nm, 2 * i);
#pragma unroll
        for (int j = 0; j < 8; j++) xr[8 * i + j] = pack2(fmaf(blo(xr[8 * i + j]), r, m), fmaf(bhi(xr[8 * i + j]), r, m));
      }
      pin(xr);
      TS(1);
      {
        const int c = ct & 127;
        unsigned long long pk[4];
#pragma unroll
        for (int i = 0; i < 4; i++) pk[i] = ld_ll(&g_sync.modll[i * 128 + c]);
#pragma unroll
        for (int i = 0; i < 4; i++) { const uint32_t w = get_ll(&g_sync.modll[i * 128 + c], pk[i], tag); sts32(sb + OFF_MODSM + (i * 128 + c) * 4, i < 2 ? w : one_plus(w)); }
      }
      bar_sync(B_WG + cw, 128);
      TS(2);
      const uint4 sa0 = lds128(sb + OFF_MODSM + lane * 16), sa1 = lds128(sb + OFF_MODSM + 512 + lane * 16);
      const uint4 ga0 = lds128(sb + OFF_MODSM + 1024 + lane * 16), ga1 = lds128(sb + OFF_MODSM + 1536 + lane * 16);
#pragma unroll
      for (int i = 0; i < 16; i++) {
        const uint32_t ad = xad + i * 128 + (((lane & 7) ^ (i & 7)) << 4);
        const uint32_t h0 = hfma2(xr[8 * i], ga0.x, sa0.x), h1 = hfma2(xr[8 * i + 1], ga0.y, sa0.y), h2 = hfma2(xr[8 * i + 2], ga0.z, sa0.z), h3 = hfma2(xr[8 * i + 3], ga0.w, sa0.w);
        const uint32_t h4 = hfma2(xr[8 * i + 4], ga1.x, sa1.x), h5 = hfma2(xr[8 * i + 5], ga1.y, sa1.y), h6 = hfma2(xr[8 * i + 6], ga1.z, sa1.z), h7 = hfma2(xr[8 * i + 7], ga1.w, sa1.w);
        sts128(ad, h0, h1, h2, h3);
        sts128(ad + 65536, h4, h5, h6, h7);
      }
      fence_async_smem();
      bar_sync(B_WG + cw, 128);
    }
    TS(3);

    const uint64_t dA0 = make_desc(sb + cw * 8192, 16, 1024);
    const uint64_t dB0 = make_desc(sb, 4096, 1024);
    uint32_t q[32];

    {
      uint32_t held[64];
      float acc[128];
      int h6 = 8, prev = 8;
#pragma unroll
      for (int pass = 0; pass < 2; pass++) {
#pragma unroll 1
        for (int k = 0; k < 16; k++) {
          wait_full(h6);
          wg_fence();
#pragma unroll
          for (int ks = 0; ks < 2; ks++) wgmma_ss_n256_t1(acc, dA0 + (k >> 1) * 1024 + (k & 1) * 4 + ks * 2, dB0 + h6 * 1024 + ks * 128, (k | ks) != 0);
          wg_commit();
          if (k > 0) { wg_wait<1>(); release(prev); }
          prev = h6; h6 = h6 == 13 ? 8 : h6 + 1;
        }
        wg_wait<0>(); pin(acc);
        release(prev);
        if (pass == 0) {
#pragma unroll
          for (int j = 0; j < 64; j++) held[j] = pack2(acc[2 * j], acc[2 * j + 1]);
          pin(held);
        }
      }
      release(6); release(7);
#pragma unroll
      for (int j = 0; j < 32; j++) q[j] = pack2(acc[2 * j], acc[2 * j + 1]);
#pragma unroll
      for (int kk = 0; kk < 8; kk++) {
        stsm4(frag_addr(0, kk), pack2(acc[64 + 8 * kk], acc[65 + 8 * kk]), pack2(acc[66 + 8 * kk], acc[67 + 8 * kk]), pack2(acc[68 + 8 * kk], acc[69 + 8 * kk]), pack2(acc[70 + 8 * kk], acc[71 + 8 * kk]));
        stsm4(frag_addr(1, kk), held[4 * kk], held[4 * kk + 1], held[4 * kk + 2], held[4 * kk + 3]);
        stsm4(frag_addr(2, kk), held[32 + 4 * kk], held[33 + 4 * kk], held[34 + 4 * kk], held[35 + 4 * kk]);
      }
      pin(q);
    }
    TS(4);

    {
      const float cl2 = 0.08838834764831845f * 1.4426950408889634f;
      const uint64_t dK0 = make_desc(sb + 5 * SLOT, 16, 1024);
      const uint64_t dV0 = make_desc(sb + 3 * SLOT, 16384, 1024);
      float o[64], s[64];
      uint32_t p[32];
      float ms0, ms1, l0, l1, t0, t1;
      auto qk = [&](int st) {
#pragma unroll
        for (int kk = 0; kk < 8; kk++) wgmma_rs_n128_t0(s, q[4 * kk], q[4 * kk + 1], q[4 * kk + 2], q[4 * kk + 3], dK0 + st * 2048 + (kk >> 2) * 1024 + (kk & 3) * 2, kk != 0);
        wg_commit();
      };
      auto pv = [&](int st, int acc) {
#pragma unroll
        for (int kk = 0; kk < 8; kk++) wgmma_rs_n128_t1(o, p[4 * kk], p[4 * kk + 1], p[4 * kk + 2], p[4 * kk + 3], dV0 + st * 2048 + kk * 128, (kk != 0) | acc);
        wg_commit();
      };
      auto rowmax = [&](float& a, float& c) {
        float u[4], w[4];
#pragma unroll
        for (int j = 0; j < 4; j++) { u[j] = fmaxf(s[4 * j], s[4 * j + 1]); w[j] = fmaxf(s[4 * j + 2], s[4 * j + 3]); }
#pragma unroll
        for (int j = 4; j < 16; j++) { u[j & 3] = fmaxf(fmaxf(u[j & 3], s[4 * j]), s[4 * j + 1]); w[j & 3] = fmaxf(fmaxf(w[j & 3], s[4 * j + 2]), s[4 * j + 3]); }
        float x0 = fmaxf(fmaxf(u[0], u[1]), fmaxf(u[2], u[3])), x1 = fmaxf(fmaxf(w[0], w[1]), fmaxf(w[2], w[3]));
        x0 = fmaxf(x0, __shfl_xor_sync(~0u, x0, 1)); x1 = fmaxf(x1, __shfl_xor_sync(~0u, x1, 1));
        x0 = fmaxf(x0, __shfl_xor_sync(~0u, x0, 2)); x1 = fmaxf(x1, __shfl_xor_sync(~0u, x1, 2));
        a = x0 * cl2; c = x1 * cl2;
      };
      auto exprange = [&](auto j0, auto j1) {
#pragma unroll
        for (int j = j0; j < j1; j++) {
          s[4 * j] = ex2(fmaf(s[4 * j], cl2, -ms0)); s[4 * j + 1] = ex2(fmaf(s[4 * j + 1], cl2, -ms0));
          s[4 * j + 2] = ex2(fmaf(s[4 * j + 2], cl2, -ms1)); s[4 * j + 3] = ex2(fmaf(s[4 * j + 3], cl2, -ms1));
          if (j == 0) { t0 = s[0] + s[1]; t1 = s[2] + s[3]; } else { t0 += s[4 * j] + s[4 * j + 1]; t1 += s[4 * j + 2] + s[4 * j + 3]; }
        }
      };
      auto expsum = [&]() { exprange(IC<0>(), IC<16>()); };
      auto cvtp = [&]() {
#pragma unroll
        for (int j = 0; j < 32; j++) p[j] = pack2(s[2 * j], s[2 * j + 1]);
      };
      auto inv_l = [&](float& i0, float& i1) {
        float a = l0 + __shfl_xor_sync(~0u, l0, 1), c = l1 + __shfl_xor_sync(~0u, l1, 1);
        a += __shfl_xor_sync(~0u, a, 2); c += __shfl_xor_sync(~0u, c, 2);
        i0 = 1.f / a; i1 = 1.f / c;
      };
      if (cw == 0) bar_arrive(B_PP, 256);
      mbar_wait(AFULL(5), 0);
      bar_sync(B_PP + cw, 256);
      wg_fence();
      qk(0);
      bar_arrive(B_PP + (cw ^ 1), 256);
      wg_wait<0>(); pin(s);
      release_a(5);
      rowmax(ms0, ms1);
      expsum();
      cvtp();
      l0 = t0; l1 = t1;
      pin(p);
      mbar_wait(AFULL(6), 0);
      TS(5);
#pragma unroll 1
      for (int t = 1; t < 64; t++) {
        const int st = t & 1;
        bar_sync(B_PP + cw, 256);
        wg_fence();
        qk(st);
        mbar_wait(AFULL(3 + st), ((t - 1) >> 1) & 1);
        wg_fence();
        pv(st, (t & 15) != 1);
        bar_arrive(B_PP + (cw ^ 1), 256);
        wg_wait<1>(); pin(s);
        release_a(5 + st);
        const bool first = (t & 15) == 0;
        float i0, i1;
        if (first) { inv_l(i0, i1); rowmax(ms0, ms1); l0 = 0.f; l1 = 0.f; }
        exprange(IC<0>(), IC<EXP_SPLIT>());
        pin(s);
        mbar_wait(AFULL(6 - st), ((t + 1 - (t == 63 ? 2 : 0)) >> 1) & 1);
        wg_wait<0>(); pin(o); pin(p);
        release_a(3 + st);
        exprange(IC<EXP_SPLIT>(), IC<16>());
        if (first) {
          const int slot = (t >> 4) - 1;
#pragma unroll
          for (int j = 0; j < 16; j++) { p[2 * j] = pack2(o[4 * j] * i0, o[4 * j + 1] * i0); p[2 * j + 1] = pack2(o[4 * j + 2] * i1, o[4 * j + 3] * i1); }
#pragma unroll
          for (int kk = 0; kk < 8; kk++) stsm4(frag_addr(slot, kk), p[4 * kk], p[4 * kk + 1], p[4 * kk + 2], p[4 * kk + 3]);
          fence_async_smem();
        }
        cvtp();
        if (__builtin_expect(__any_sync(~0u, !(t0 + t1 <= 1.2089258e24f)), 0)) {
          const uint32_t* kp = (const uint32_t*)(kc + (size_t)(g * SEQ + (t & 15) * 128 + (lane >> 2)) * DH) + (lane & 3);
#pragma unroll
          for (int j = 0; j < 16; j++) {
            s[4 * j] = 0.f; s[4 * j + 1] = 0.f; s[4 * j + 2] = 0.f; s[4 * j + 3] = 0.f;
#pragma unroll
            for (int kk = 0; kk < 8; kk++)
              mma16816(s[4 * j], s[4 * j + 1], s[4 * j + 2], s[4 * j + 3], q[4 * kk], q[4 * kk + 1], q[4 * kk + 2], q[4 * kk + 3], ldg_nc32(kp + j * 512 + kk * 8), ldg_nc32(kp + j * 512 + kk * 8 + 4));
          }
          float x0, x1;
          rowmax(x0, x1);
          x0 = fmaxf(x0, ms0); x1 = fmaxf(x1, ms1);
          const float a0 = ex2(ms0 - x0), a1 = ex2(ms1 - x1);
          ms0 = x0; ms1 = x1; l0 *= a0; l1 *= a1;
#pragma unroll
          for (int j = 0; j < 16; j++) { o[4 * j] *= a0; o[4 * j + 1] *= a0; o[4 * j + 2] *= a1; o[4 * j + 3] *= a1; }
          expsum();
          cvtp();
        }
        l0 += t0; l1 += t1;
        if ((t & 15) == 15 && t < 63) {
#pragma unroll
          for (int kk = 0; kk < 8; kk++) ldsm4(frag_addr(t >> 4, kk), q[4 * kk], q[4 * kk + 1], q[4 * kk + 2], q[4 * kk + 3]);
        }
        pin(p); pin(o); pin(q);
        asm volatile("" : "+f"(l0), "+f"(l1) :: "memory");
      }
      mbar_wait(AFULL(3), 1);
      if (cw == 0) bar_sync(B_PP, 256);
      wg_fence();
      pv(0, 1);
      float i0, i1;
      inv_l(i0, i1);
      wg_wait<0>(); pin(o);
      release_a(3);
#pragma unroll
      for (int j = 0; j < 16; j++) { q[2 * j] = pack2(o[4 * j] * i0, o[4 * j + 1] * i0); q[2 * j + 1] = pack2(o[4 * j + 2] * i1, o[4 * j + 3] * i1); }
      pin(q);
    }
    TS(10);

    uint4* const part_w = g_part + ((size_t)(rt * 8 + wid) * 8 + g) * 1024 + lane;
    auto store_part = [&](const float (&acc)[128], int pass) {
#pragma unroll
      for (int c = 0; c < 16; c++)
        stg128(part_w + (pass * 16 + c) * 32, pack2(acc[8 * c], acc[8 * c + 1]), pack2(acc[8 * c + 2], acc[8 * c + 3]), pack2(acc[8 * c + 4], acc[8 * c + 5]), pack2(acc[8 * c + 6], acc[8 * c + 7]));
    };
    auto publish = [&](int phase) {
      bar_sync(B_CONS, 256);
      if (ct == 0) flag_set(&g_sync.flag[(phase * 16 + rt) * 32 + g], tag);
    };
    auto gather = [&](float (&y)[32]) {
#pragma unroll
      for (int sg = 0; sg < 8; sg++) {
        wait_full(sg);
#pragma unroll
        for (int c = 0; c < 4; c++) {
          const uint4 w = lds128(sb + sg * HALF + wid * 2048 + c * 512 + lane * 16);
          if (sg == 0) {
            y[8 * c] = blo(w.x); y[8 * c + 1] = bhi(w.x); y[8 * c + 2] = blo(w.y); y[8 * c + 3] = bhi(w.y);
            y[8 * c + 4] = blo(w.z); y[8 * c + 5] = bhi(w.z); y[8 * c + 6] = blo(w.w); y[8 * c + 7] = bhi(w.w);
          } else {
            y[8 * c] += blo(w.x); y[8 * c + 1] += bhi(w.x); y[8 * c + 2] += blo(w.y); y[8 * c + 3] += bhi(w.y);
            y[8 * c + 4] += blo(w.z); y[8 * c + 5] += bhi(w.z); y[8 * c + 6] += blo(w.w); y[8 * c + 7] += bhi(w.w);
          }
        }
      }
    };
    auto write_rows = [&](const uint32_t (&w)[16], __nv_bfloat16* dst) {
      const uint32_t st = sb + wid * 2048;
      __syncwarp();
#pragma unroll
      for (int c = 0; c < 4; c++) stsm4(st + (lane & 15) * 128 + (((c * 2 + (lane >> 4)) ^ (lane & 7)) << 4), w[4 * c], w[4 * c + 1], w[4 * c + 2], w[4 * c + 3]);
      __syncwarp();
#pragma unroll
      for (int i = 0; i < 4; i++) {
        const int r = i * 4 + (lane >> 3);
        const uint4 u = lds128(st + r * 128 + (((lane & 7) ^ (r & 7)) << 4));
        stg128(dst + (size_t)(rt * 128 + g * 16 + r) * DM + wid * 64 + (lane & 7) * 8, u.x, u.y, u.z, u.w);
      }
    };
    const int mcol = wid * 32 + (lane & 3);

    {
      float acc[128];
#pragma unroll 1
      for (int pass = 0; pass < 2; pass++) {
        int prev = 0;
#pragma unroll 1
        for (int k = 0; k < 12; k++) {
          const int h = (0x7698dcba >> ((k & 7) * 4)) & 15;
          wait_full(h);
          wg_fence();
#pragma unroll
          for (int ks = 0; ks < 2; ks++) wgmma_ss_n256_t1(acc, dA0 + (k >> 1) * 1024 + (k & 1) * 4 + ks * 2, dB0 + h * 1024 + ks * 128, (k | ks) != 0);
          wg_commit();
          if (k > 0) { wg_wait<1>(); release(prev); }
          prev = h;
        }
#pragma unroll
        for (int k = 0; k < 4; k++) {
          const int h = k < 2 ? 8 + k : 4 + k;
          wait_full(h);
          wg_fence();
#pragma unroll
          for (int ks = 0; ks < 2; ks++) wgmma_rs_n256_t1(acc, q[8 * k + 4 * ks], q[8 * k + 4 * ks + 1], q[8 * k + 4 * ks + 2], q[8 * k + 4 * ks + 3], dB0 + h * 1024 + ks * 128, 1);
          wg_commit();
          wg_wait<1>();
          if (k < 3 || pass == 0) release(k == 0 ? 13 : k == 1 ? 8 : k == 2 ? 9 : 6);
        }
        wg_wait<0>(); pin(acc); pin(q);
        if (pass == 0) release(7); else bar_arrive(B_X, 288);
        store_part(acc, pass);
      }
    }
    publish(0);
    TS(11);

    uint32_t x1[16];
    {
      uint32_t ga[8], cb[8], sbv[8];
      {
        unsigned long long pg[8], ps[8], pc[8];
#pragma unroll
        for (int j = 0; j < 8; j++) { pg[j] = ld_ll(&g_sync.modll[512 + mcol + 4 * j]); ps[j] = ld_ll(&g_sync.modll[768 + mcol + 4 * j]); pc[j] = ld_ll(&g_sync.modll[1024 + mcol + 4 * j]); }
        const uint32_t* xp = (const uint32_t*)(x + (size_t)(rt * 128 + g * 16 + (lane >> 2)) * DM) + mcol;
#pragma unroll
        for (int j = 0; j < 8; j++) { x1[2 * j] = ldg_nc32(xp + 4 * j); x1[2 * j + 1] = ldg_nc32(xp + 8 * (DM / 2) + 4 * j); }
#pragma unroll
        for (int j = 0; j < 8; j++) {
          ga[j] = get_ll(&g_sync.modll[512 + mcol + 4 * j], pg[j], tag); sbv[j] = get_ll(&g_sync.modll[768 + mcol + 4 * j], ps[j], tag);
          cb[j] = one_plus(get_ll(&g_sync.modll[1024 + mcol + 4 * j], pc[j], tag));
        }
      }
      float y[32];
      gather(y);
      TS(12);
      float s0 = 0.f, q0 = 0.f, s1 = 0.f, q1 = 0.f;
#pragma unroll
      for (int j = 0; j < 8; j++) {
        x1[2 * j] = pack2(fmaf(blo(ga[j]), y[4 * j], blo(x1[2 * j])), fmaf(bhi(ga[j]), y[4 * j + 1], bhi(x1[2 * j])));
        x1[2 * j + 1] = pack2(fmaf(blo(ga[j]), y[4 * j + 2], blo(x1[2 * j + 1])), fmaf(bhi(ga[j]), y[4 * j + 3], bhi(x1[2 * j + 1])));
        y[4 * j] = blo(x1[2 * j]); y[4 * j + 1] = bhi(x1[2 * j]); y[4 * j + 2] = blo(x1[2 * j + 1]); y[4 * j + 3] = bhi(x1[2 * j + 1]);
        s0 += y[4 * j] + y[4 * j + 1]; q0 = fmaf(y[4 * j], y[4 * j], q0); q0 = fmaf(y[4 * j + 1], y[4 * j + 1], q0);
        s1 += y[4 * j + 2] + y[4 * j + 3]; q1 = fmaf(y[4 * j + 2], y[4 * j + 2], q1); q1 = fmaf(y[4 * j + 3], y[4 * j + 3], q1);
      }
#pragma unroll
      for (int o = 1; o < 4; o <<= 1) { s0 += __shfl_xor_sync(~0u, s0, o); q0 += __shfl_xor_sync(~0u, q0, o); s1 += __shfl_xor_sync(~0u, s1, o); q1 += __shfl_xor_sync(~0u, q1, o); }
      if ((lane & 3) == 0) sts128(sb + OFF_MODSM + (wid * 8 + (lane >> 2)) * 16, __float_as_uint(s0), __float_as_uint(q0), __float_as_uint(s1), __float_as_uint(q1));
      bar_sync(B_CONS, 256);
      s0 = q0 = s1 = q1 = 0.f;
#pragma unroll
      for (int w = 0; w < 8; w++) { const uint4 u = lds128(sb + OFF_MODSM + (w * 8 + (lane >> 2)) * 16); s0 += __uint_as_float(u.x); q0 += __uint_as_float(u.y); s1 += __uint_as_float(u.z); q1 += __uint_as_float(u.w); }
      const float m0 = s0 * (1.f / DM), m1 = s1 * (1.f / DM);
      const float r0 = 1.f / bround(sqrtf(bround(bround(fmaxf(q0 * (1.f / DM) - m0 * m0, 0.f)) + 1e-5f)));
      const float r1 = 1.f / bround(sqrtf(bround(bround(fmaxf(q1 * (1.f / DM) - m1 * m1, 0.f)) + 1e-5f)));
      const float n0 = -bround(m0) * r0, n1 = -bround(m1) * r1;
      uint32_t hw[16];
#pragma unroll
      for (int j = 0; j < 8; j++) {
        hw[2 * j] = hfma2(pack2(fmaf(y[4 * j], r0, n0), fmaf(y[4 * j + 1], r0, n0)), cb[j], sbv[j]);
        hw[2 * j + 1] = hfma2(pack2(fmaf(y[4 * j + 2], r1, n1), fmaf(y[4 * j + 3], r1, n1)), cb[j], sbv[j]);
      }
      write_rows(hw, g_h2);
      bar_arrive(B_X, 288);
      publish(1);
      pin(x1);
    }
    TS(13);

    {
      uint32_t act[56];
      int h6 = 10, prev = 10;
      auto swiglu = [&](float gt0, float gt1, float up0, float up1) {
        const float h0 = 0.5f * gt0, h1 = 0.5f * gt1;
        return pack2(fmaf(h0, tanh_fast(h0), h0) * up0, fmaf(h1, tanh_fast(h1), h1) * up1);
      };
      {
        float acc[128];
#pragma unroll 1
        for (int k = 0; k < 16; k++) {
          if ((k & 1) == 0) wait_full(k >> 1);
          wait_full(h6);
          wg_fence();
#pragma unroll
          for (int ks = 0; ks < 2; ks++) wgmma_ss_n256_t1(acc, dA0 + (k >> 1) * 1024 + (k & 1) * 4 + ks * 2, dB0 + h6 * 1024 + ks * 128, (k | ks) != 0);
          wg_commit();
          if (k > 0) { wg_wait<1>(); release(prev); }
          prev = h6; h6 = h6 == 13 ? 8 : h6 + 1;
          if (k == 0) TS(14);
        }
        wg_wait<0>(); pin(acc);
        release(prev);
        TS(20);
#pragma unroll
        for (int j = 0; j < 32; j++) act[j] = swiglu(acc[2 * j], acc[2 * j + 1], acc[64 + 2 * j], acc[65 + 2 * j]);
      }
      {
        float ag[48], au[48];
#pragma unroll 1
        for (int k = 0; k < 16; k++) {
          wait_full(h6);
          wg_fence();
#pragma unroll
          for (int ks = 0; ks < 2; ks++) {
            wgmma_ss_n96_t1(ag, dA0 + (k >> 1) * 1024 + (k & 1) * 4 + ks * 2, dB0 + h6 * 1024 + ks * 128, (k | ks) != 0);
            wgmma_ss_n96_t1(au, dA0 + (k >> 1) * 1024 + (k & 1) * 4 + ks * 2, dB0 + h6 * 1024 + 512 + ks * 128, (k | ks) != 0);
          }
          wg_commit();
          if (k > 0) { wg_wait<1>(); release(prev); if ((k & 1) == 0) release((k >> 1) - 1); }
          prev = h6; h6 = h6 == 13 ? 8 : h6 + 1;
        }
        wg_wait<0>(); pin(ag); pin(au);
        release(prev); release(7);
        TS(21);
#pragma unroll
        for (int j = 0; j < 24; j++) act[32 + j] = swiglu(ag[2 * j], ag[2 * j + 1], au[2 * j], au[2 * j + 1]);
      }
      pin(act);
      TS(15);
      float acc[128];
#pragma unroll 1
      for (int pass = 0; pass < 2; pass++) {
#pragma unroll
        for (int k = 0; k < 7; k++) {
          const int h = pass == 0 ? k : (0xba98dc7 >> (k * 4)) & 15;
          wait_full(h);
          wg_fence();
#pragma unroll
          for (int ks = 0; ks < 2; ks++) wgmma_rs_n256_t1(acc, act[8 * k + 4 * ks], act[8 * k + 4 * ks + 1], act[8 * k + 4 * ks + 2], act[8 * k + 4 * ks + 3], dB0 + h * 1024 + ks * 128, (k | ks) != 0);
        }
        wg_commit();
        wg_wait<0>(); pin(acc); pin(act);
        if (pass == 1) bar_arrive(B_X, 288);
        store_part(acc, pass);
      }
    }
    publish(2);
    asm volatile("barrier.cluster.arrive.relaxed.aligned;" ::: "memory");
    TS(16);

    {
      uint32_t gb[8];
      {
        unsigned long long pg[8];
#pragma unroll
        for (int j = 0; j < 8; j++) pg[j] = ld_ll(&g_sync.modll[1280 + mcol + 4 * j]);
#pragma unroll
        for (int j = 0; j < 8; j++) gb[j] = get_ll(&g_sync.modll[1280 + mcol + 4 * j], pg[j], tag);
      }
      float y[32];
      gather(y);
      TS(17);
      if (b == 0 && ct == 0) g_sync.epoch = tag;
      uint32_t ow[16];
#pragma unroll
      for (int j = 0; j < 8; j++) {
        ow[2 * j] = pack2(fmaf(blo(gb[j]), y[4 * j], blo(x1[2 * j])), fmaf(bhi(gb[j]), y[4 * j + 1], bhi(x1[2 * j])));
        ow[2 * j + 1] = pack2(fmaf(blo(gb[j]), y[4 * j + 2], blo(x1[2 * j + 1])), fmaf(bhi(gb[j]), y[4 * j + 3], bhi(x1[2 * j + 1])));
      }
      write_rows(ow, out);
    }
    TS(18);
    asm volatile("barrier.cluster.wait.aligned;" ::: "memory");
  }
}

typedef CUresult (*EncodeFn)(CUtensorMap*, CUtensorMapDataType, cuuint32_t, void*, const cuuint64_t*, const cuuint64_t*, const cuuint32_t*, const cuuint32_t*,
                             CUtensorMapInterleave, CUtensorMapSwizzle, CUtensorMapL2promotion, CUtensorMapFloatOOBfill);

void make_map(EncodeFn fn, CUtensorMap* m, const void* p, uint64_t rows, uint64_t cols, uint32_t box_rows) {
  cuuint64_t dims[2] = {cols, rows};
  cuuint64_t strides[1] = {cols * 2};
  cuuint32_t box[2] = {64, box_rows};
  cuuint32_t es[2] = {1, 1};
  fn(m, CU_TENSOR_MAP_DATA_TYPE_BFLOAT16, 2, const_cast<void*>(p), dims, strides, box, es, CU_TENSOR_MAP_INTERLEAVE_NONE, CU_TENSOR_MAP_SWIZZLE_128B,
     CU_TENSOR_MAP_L2_PROMOTION_L2_128B, CU_TENSOR_MAP_FLOAT_OOB_FILL_NONE);
}

}

extern "C" void kernel_launch(void* const* d_in, const int* in_sizes, int n_in, void* d_out, int out_size) {
  (void)in_sizes; (void)n_in; (void)out_size;
  typedef const __nv_bfloat16* P;
  P x = (P)d_in[0], k = (P)d_in[1], v = (P)d_in[2], wq = (P)d_in[3], wo = (P)d_in[4];
  P wg = (P)d_in[6], wu = (P)d_in[7], wd = (P)d_in[8], c = (P)d_in[9], wmod = (P)d_in[10];
  static EncodeFn fn = nullptr;
  static void* h2p = nullptr;
  if (!fn) {
    void* p = nullptr;
    cudaDriverEntryPointQueryResult qr;
    cudaGetDriverEntryPoint("cuTensorMapEncodeTiled", &p, cudaEnableDefault, &qr);
    fn = (EncodeFn)p;
    cudaGetSymbolAddress(&h2p, g_h2);
    cudaFuncSetAttribute(fused_kernel, cudaFuncAttributeMaxDynamicSharedMemorySize, SMEM_BYTES);
  }
  Maps mp;
  make_map(fn, &mp.wq, wq, 512, 4096, 32);
  make_map(fn, &mp.k, k, 8 * SEQ, DH, 128);
  make_map(fn, &mp.v, v, 8 * SEQ, DH, 128);
  make_map(fn, &mp.wo, wo, 4096, DM, 32);
  make_map(fn, &mp.wg, wg, DM, FF, 32);
  make_map(fn, &mp.wu, wu, DM, FF, 32);
  make_map(fn, &mp.wd, wd, FF, DM, 32);
  make_map(fn, &mp.h2, h2p, SEQ, DM, 16);
  make_map(fn, &mp.x, x, SEQ, DM, 32);
  fused_kernel<<<128, 384, SMEM_BYTES>>>(mp, x, k, wo, wg, wu, wd, c, wmod, (__nv_bfloat16*)d_out);
}
```

```cpp
#include <cuda_runtime.h>
#include <cuda_bf16.h>
#include <cuda.h>
#include <stdint.h>

namespace {

constexpr int SEQ = 2048, DM = 512, DH = 128, FF = 1792, FS = 224;
constexpr int SLOT = 32768, HALF = 16384;
constexpr int OFF_BAR = 7 * SLOT;
constexpr int OFF_MODSM = OFF_BAR + 320;
constexpr int OFF_RED = OFF_MODSM + 2048;
constexpr int OFF_RED2 = OFF_RED + 256;
constexpr int OFF_EPOCH = OFF_RED2 + 192;
constexpr int SMEM_BYTES = 232448;
static_assert(OFF_EPOCH + 16 <= SMEM_BYTES, "smem");

constexpr int CONS_REGS = 232, PROD_REGS = 40;
#define EXP_SPLIT 11

__device__ uint4 g_part[16 * 8 * 8 * 1024];
__device__ __nv_bfloat16 g_h2[SEQ * DM];
struct __align__(128) Sync {
  unsigned long long modll[512];
  unsigned int late[1024];
  unsigned int flag[3 * 16 * 32];
  unsigned int late_cnt;
  unsigned int pad[31];
  unsigned int epoch;
};
__device__ Sync g_sync;

struct Maps { CUtensorMap wq, k, v, wo, wg, wu, wd, h2, x; };

__device__ __forceinline__ uint32_t smem_u32(const void* p) { return (uint32_t)__cvta_generic_to_shared(p); }
__device__ __forceinline__ void mbar_init(uint32_t bar, uint32_t cnt) { asm volatile("mbarrier.init.shared::cta.b64 [%0], %1;" :: "r"(bar), "r"(cnt) : "memory"); }
__device__ __forceinline__ void mbar_expect_tx(uint32_t bar, uint32_t bytes) { asm volatile("mbarrier.arrive.expect_tx.shared::cta.b64 _, [%0], %1;" :: "r"(bar), "r"(bytes) : "memory"); }
__device__ __forceinline__ void mbar_wait(uint32_t bar, uint32_t par) {
  asm volatile(
    "{\n.reg .pred p;\n.reg .u32 n;\n"
    "mov.u32 n, 0;\n"
    "W_LOOP:\n"
    "mbarrier.try_wait.parity.shared::cta.b64 p, [%0], %1;\n"
    "@p bra W_DONE;\n"
    "add.u32 n, n, 1;\n"
    "setp.lt.u32 p, n, 0x1000000;\n"
    "@p bra W_LOOP;\n"
    "trap;\n"
    "W_DONE:\n}" :: "r"(bar), "r"(par) : "memory");
}
__device__ __forceinline__ void tma_load(uint32_t dst, const CUtensorMap* m, uint32_t bar, int c0, int c1) {
  asm volatile("cp.async.bulk.tensor.2d.shared::cluster.global.mbarrier::complete_tx::bytes [%0], [%1, {%3, %4}], [%2];" :: "r"(dst), "l"(m), "r"(bar), "r"(c0), "r"(c1) : "memory");
}
__device__ __forceinline__ void tma_load_mc(uint32_t dst, const CUtensorMap* m, uint32_t bar, int c0, int c1) {
  asm volatile("cp.async.bulk.tensor.2d.shared::cluster.global.mbarrier::complete_tx::bytes.multicast::cluster [%0], [%1, {%3, %4}], [%2], %5;" :: "r"(dst), "l"(m), "r"(bar), "r"(c0), "r"(c1), "h"((uint16_t)3) : "memory");
}
__device__ __forceinline__ void tma_prefetch(const CUtensorMap* m, int c0, int c1) {
  asm volatile("cp.async.bulk.prefetch.tensor.2d.L2.global [%0, {%1, %2}];" :: "l"(m), "r"(c0), "r"(c1) : "memory");
}
__device__ __forceinline__ void bulk_prefetch(const void* p, uint32_t bytes) {
  asm volatile("cp.async.bulk.prefetch.L2.global [%0], %1;" :: "l"(p), "r"(bytes) : "memory");
}
__device__ __forceinline__ void bulk_load(uint32_t dst, const void* src, uint32_t bytes, uint32_t bar) {
  asm volatile("cp.async.bulk.shared::cluster.global.mbarrier::complete_tx::bytes [%0], [%1], %2, [%3];" :: "r"(dst), "l"(src), "r"(bytes), "r"(bar) : "memory");
}
__device__ __forceinline__ void fence_async_smem() { asm volatile("fence.proxy.async.shared::cta;" ::: "memory"); }
__device__ __forceinline__ void fence_gpu() { asm volatile("fence.acq_rel.gpu;" ::: "memory"); }
__device__ __forceinline__ void bar_sync(int id, int n) { asm volatile("bar.sync %0, %1;" :: "r"(id), "r"(n) : "memory"); }
__device__ __forceinline__ void bar_arrive(int id, int n) { asm volatile("bar.arrive %0, %1;" :: "r"(id), "r"(n) : "memory"); }
__device__ __forceinline__ void wg_fence() { asm volatile("wgmma.fence.sync.aligned;" ::: "memory"); }
__device__ __forceinline__ void wg_commit() { asm volatile("wgmma.commit_group.sync.aligned;" ::: "memory"); }
template <int N> __device__ __forceinline__ void wg_wait() { asm volatile("wgmma.wait_group.sync.aligned %0;" :: "n"(N) : "memory"); }
template <int N> __device__ __forceinline__ void pin(float (&r)[N]) {
#pragma unroll
  for (int i = 0; i < N; i++) asm volatile("" : "+f"(r[i]) :: "memory");
}
template <int N> __device__ __forceinline__ void pin(uint32_t (&r)[N]) {
#pragma unroll
  for (int i = 0; i < N; i++) asm volatile("" : "+r"(r[i]) :: "memory");
}
__device__ __forceinline__ uint64_t make_desc(uint32_t addr, uint32_t lbo, uint32_t sbo) {
  return (uint64_t)((addr & 0x3FFFF) >> 4) | ((uint64_t)(lbo >> 4) << 16) | ((uint64_t)(sbo >> 4) << 32) | (1ull << 62);
}
__device__ __forceinline__ float ex2(float x) { float y; asm("ex2.approx.ftz.f32 %0, %1;" : "=f"(y) : "f"(x)); return y; }
__device__ __forceinline__ float tanh_fast(float x) { float y; asm("tanh.approx.f32 %0, %1;" : "=f"(y) : "f"(x)); return y; }
__device__ __forceinline__ uint32_t pack2(float lo, float hi) { uint32_t r; asm("cvt.rn.bf16x2.f32 %0, %1, %2;" : "=r"(r) : "f"(hi), "f"(lo)); return r; }
__device__ __forceinline__ float blo(uint32_t w) { return __uint_as_float(w << 16); }
__device__ __forceinline__ float bhi(uint32_t w) { return __uint_as_float(w & 0xffff0000u); }
__device__ __forceinline__ float bround(float x) { return blo(pack2(x, 0.f)); }
__device__ __forceinline__ uint32_t hfma2(uint32_t a, uint32_t b, uint32_t c) { uint32_t r; asm("fma.rn.bf16x2 %0, %1, %2, %3;" : "=r"(r) : "r"(a), "r"(b), "r"(c)); return r; }
__device__ __forceinline__ uint32_t one_plus(uint32_t w) { return pack2(1.f + blo(w), 1.f + bhi(w)); }
__device__ __forceinline__ void ldsm4(uint32_t addr, uint32_t& a, uint32_t& b, uint32_t& c, uint32_t& d) {
  asm volatile("ldmatrix.sync.aligned.m8n8.x4.shared.b16 {%0,%1,%2,%3}, [%4];" : "=r"(a), "=r"(b), "=r"(c), "=r"(d) : "r"(addr) : "memory");
}
__device__ __forceinline__ void stsm4(uint32_t addr, uint32_t a, uint32_t b, uint32_t c, uint32_t d) {
  asm volatile("stmatrix.sync.aligned.m8n8.x4.shared.b16 [%0], {%1,%2,%3,%4};" :: "r"(addr), "r"(a), "r"(b), "r"(c), "r"(d) : "memory");
}
__device__ __forceinline__ void sts128(uint32_t addr, uint32_t a, uint32_t b, uint32_t c, uint32_t d) {
  asm volatile("st.shared.v4.b32 [%0], {%1,%2,%3,%4};" :: "r"(addr), "r"(a), "r"(b), "r"(c), "r"(d) : "memory");
}
__device__ __forceinline__ uint4 lds128(uint32_t addr) {
  uint4 v; asm volatile("ld.shared.v4.b32 {%0,%1,%2,%3}, [%4];" : "=r"(v.x), "=r"(v.y), "=r"(v.z), "=r"(v.w) : "r"(addr) : "memory"); return v;
}
__device__ __forceinline__ void sts32(uint32_t addr, uint32_t v) { asm volatile("st.shared.b32 [%0], %1;" :: "r"(addr), "r"(v) : "memory"); }
__device__ __forceinline__ uint32_t lds32(uint32_t addr) { uint32_t v; asm volatile("ld.shared.b32 %0, [%1];" : "=r"(v) : "r"(addr) : "memory"); return v; }
__device__ __forceinline__ uint4 ldg_nc128(const void* p) {
  uint4 v; asm volatile("ld.global.nc.v4.b32 {%0,%1,%2,%3}, [%4];" : "=r"(v.x), "=r"(v.y), "=r"(v.z), "=r"(v.w) : "l"(p)); return v;
}
__device__ __forceinline__ uint32_t ldg_nc32(const void* p) { uint32_t v; asm volatile("ld.global.nc.b32 %0, [%1];" : "=r"(v) : "l"(p)); return v; }
__device__ __forceinline__ void stg128(void* p, uint32_t a, uint32_t b, uint32_t c, uint32_t d) {
  asm volatile("st.global.v4.b32 [%0], {%1,%2,%3,%4};" :: "l"(p), "r"(a), "r"(b), "r"(c), "r"(d) : "memory");
}
__device__ __forceinline__ unsigned long long ld_ll(const unsigned long long* p) {
  unsigned long long v; asm volatile("ld.relaxed.gpu.global.b64 %0, [%1];" : "=l"(v) : "l"(p) : "memory"); return v;
}
__device__ __forceinline__ void st_ll(unsigned long long* p, uint32_t val, uint32_t tag) {
  asm volatile("st.relaxed.gpu.global.b64 [%0], %1;" :: "l"(p), "l"(((unsigned long long)tag << 32) | val) : "memory");
}
__device__ __forceinline__ void flag_set(unsigned int* f, uint32_t tag) { asm volatile("st.release.gpu.global.u32 [%0], %1;" :: "l"(f), "r"(tag) : "memory"); }
__device__ __forceinline__ uint32_t flag_get(const unsigned int* f) { uint32_t v; asm volatile("ld.relaxed.gpu.global.u32 %0, [%1];" : "=r"(v) : "l"(f) : "memory"); return v; }
__device__ __forceinline__ void trap_if(bool c) { asm volatile("{\n.reg .pred p;\nsetp.ne.u32 p, %0, 0;\n@p trap;\n}" :: "r"((uint32_t)c)); }
__device__ __forceinline__ float rcp_fast(float x) { float y; asm("rcp.approx.ftz.f32 %0, %1;" : "=f"(y) : "f"(x)); return y; }
__device__ __forceinline__ float sqrt_fast(float x) { float y; asm("sqrt.approx.ftz.f32 %0, %1;" : "=f"(y) : "f"(x)); return y; }
__device__ __forceinline__ float silu_bf(float x) { return bround(x * rcp_fast(1.f + ex2(-1.4426950408889634f * x))); }
__device__ __forceinline__ float ln_rstd(float mean, float ex2mean) { return rcp_fast(bround(sqrt_fast(bround(bround(fmaxf(ex2mean - mean * mean, 0.f)) + 1e-5f)))); }
__device__ __forceinline__ uint4 ldg_cg128(const void* p) {
  uint4 v; asm volatile("ld.global.cg.v4.b32 {%0,%1,%2,%3}, [%4];" : "=r"(v.x), "=r"(v.y), "=r"(v.z), "=r"(v.w) : "l"(p) : "memory"); return v;
}
__device__ __forceinline__ float xreduce8(float (&a)[8], int lane) {
#pragma unroll
  for (int i = 0; i < 4; i++) { const bool up = lane & 16; const float snd = up ? a[i] : a[i + 4], kp = up ? a[i + 4] : a[i]; a[i] = kp + __shfl_xor_sync(~0u, snd, 16); }
#pragma unroll
  for (int i = 0; i < 2; i++) { const bool up = lane & 8; const float snd = up ? a[i] : a[i + 2], kp = up ? a[i + 2] : a[i]; a[i] = kp + __shfl_xor_sync(~0u, snd, 8); }
  const bool up = lane & 4; const float snd = up ? a[0] : a[1], kp = up ? a[1] : a[0];
  const float r = kp + __shfl_xor_sync(~0u, snd, 4);
  return r + __shfl_xor_sync(~0u, r, 2);
}
__device__ __forceinline__ void mma16816(float& c0, float& c1, float& c2, float& c3, uint32_t a0, uint32_t a1, uint32_t a2, uint32_t a3, uint32_t b0, uint32_t b1) {
  asm("mma.sync.aligned.m16n8k16.row.col.f32.bf16.bf16.f32 {%0,%1,%2,%3}, {%4,%5,%6,%7}, {%8,%9}, {%0,%1,%2,%3};"
      : "+f"(c0), "+f"(c1), "+f"(c2), "+f"(c3) : "r"(a0), "r"(a1), "r"(a2), "r"(a3), "r"(b0), "r"(b1));
}

template <int N> struct IC { __device__ constexpr operator int() const { return N; } };

__device__ __forceinline__ void wgmma_rs_n128_t0(float (&d)[64], uint32_t a0, uint32_t a1, uint32_t a2, uint32_t a3, uint64_t db, int scale_d) {
  asm volatile(
    "{\n.reg .pred p;\nsetp.ne.b32 p, %69, 0;\n"
    "wgmma.mma_async.sync.aligned.m64n128k16.f32.bf16.bf16 {"
    "%0, %1, %2, %3, %4, %5, %6, %7, %8, %9, %10, %11, %12, %13, %14, %15, "
    "%16, %17, %18, %19, %20, %21, %22, %23, %24, %25, %26, %27, %28, %29, %30, %31, "
    "%32, %33, %34, %35, %36, %37, %38, %39, %40, %41, %42, %43, %44, %45, %46, %47, "
    "%48, %49, %50, %51, %52, %53, %54, %55, %56, %57, %58, %59, %60, %61, %62, %63"
    "}, {%64, %65, %66, %67}, %68, p, 1, 1, 0;\n}\n"
    : "+f"(d[0]), "+f"(d[1]), "+f"(d[2]), "+f"(d[3]), "+f"(d[4]), "+f"(d[5]), "+f"(d[6]), "+f"(d[7]),
      "+f"(d[8]), "+f"(d[9]), "+f"(d[10]), "+f"(d[11]), "+f"(d[12]), "+f"(d[13]), "+f"(d[14]), "+f"(d[15]),
      "+f"(d[16]), "+f"(d[17]), "+f"(d[18]), "+f"(d[19]), "+f"(d[20]), "+f"(d[21]), "+f"(d[22]), "+f"(d[23]),
      "+f"(d[24]), "+f"(d[25]), "+f"(d[26]), "+f"(d[27]), "+f"(d[28]), "+f"(d[29]), "+f"(d[30]), "+f"(d[31]),
      "+f"(d[32]), "+f"(d[33]), "+f"(d[34]), "+f"(d[35]), "+f"(d[36]), "+f"(d[37]), "+f"(d[38]), "+f"(d[39]),
      "+f"(d[40]), "+f"(d[41]), "+f"(d[42]), "+f"(d[43]), "+f"(d[44]), "+f"(d[45]), "+f"(d[46]), "+f"(d[47]),
      "+f"(d[48]), "+f"(d[49]), "+f"(d[50]), "+f"(d[51]), "+f"(d[52]), "+f"(d[53]), "+f"(d[54]), "+f"(d[55]),
      "+f"(d[56]), "+f"(d[57]), "+f"(d[58]), "+f"(d[59]), "+f"(d[60]), "+f"(d[61]), "+f"(d[62]), "+f"(d[63])
    : "r"(a0), "r"(a1), "r"(a2), "r"(a3), "l"(db), "r"(scale_d));
}
__device__ __forceinline__ void wgmma_rs_n128_t1(float (&d)[64], uint32_t a0, uint32_t a1, uint32_t a2, uint32_t a3, uint64_t db, int scale_d) {
  asm volatile(
    "{\n.reg .pred p;\nsetp.ne.b32 p, %69, 0;\n"
    "wgmma.mma_async.sync.aligned.m64n128k16.f32.bf16.bf16 {"
    "%0, %1, %2, %3, %4, %5, %6, %7, %8, %9, %10, %11, %12, %13, %14, %15, "
    "%16, %17, %18, %19, %20, %21, %22, %23, %24, %25, %26, %27, %28, %29, %30, %31, "
    "%32, %33, %34, %35, %36, %37, %38, %39, %40, %41, %42, %43, %44, %45, %46, %47, "
    "%48, %49, %50, %51, %52, %53, %54, %55, %56, %57, %58, %59, %60, %61, %62, %63"
    "}, {%64, %65, %66, %67}, %68, p, 1, 1, 1;\n}\n"
    : "+f"(d[0]), "+f"(d[1]), "+f"(d[2]), "+f"(d[3]), "+f"(d[4]), "+f"(d[5]), "+f"(d[6]), "+f"(d[7]),
      "+f"(d[8]), "+f"(d[9]), "+f"(d[10]), "+f"(d[11]), "+f"(d[12]), "+f"(d[13]), "+f"(d[14]), "+f"(d[15]),
      "+f"(d[16]), "+f"(d[17]), "+f"(d[18]), "+f"(d[19]), "+f"(d[20]), "+f"(d[21]), "+f"(d[22]), "+f"(d[23]),
      "+f"(d[24]), "+f"(d[25]), "+f"(d[26]), "+f"(d[27]), "+f"(d[28]), "+f"(d[29]), "+f"(d[30]), "+f"(d[31]),
      "+f"(d[32]), "+f"(d[33]), "+f"(d[34]), "+f"(d[35]), "+f"(d[36]), "+f"(d[37]), "+f"(d[38]), "+f"(d[39]),
      "+f"(d[40]), "+f"(d[41]), "+f"(d[42]), "+f"(d[43]), "+f"(d[44]), "+f"(d[45]), "+f"(d[46]), "+f"(d[47]),
      "+f"(d[48]), "+f"(d[49]), "+f"(d[50]), "+f"(d[51]), "+f"(d[52]), "+f"(d[53]), "+f"(d[54]), "+f"(d[55]),
      "+f"(d[56]), "+f"(d[57]), "+f"(d[58]), "+f"(d[59]), "+f"(d[60]), "+f"(d[61]), "+f"(d[62]), "+f"(d[63])
    : "r"(a0), "r"(a1), "r"(a2), "r"(a3), "l"(db), "r"(scale_d));
}
__device__ __forceinline__ void wgmma_ss_n256_t1(float (&d)[128], uint64_t da, uint64_t db, int scale_d) {
  asm volatile(
    "{\n.reg .pred p;\nsetp.ne.b32 p, %130, 0;\n"
    "wgmma.mma_async.sync.aligned.m64n256k16.f32.bf16.bf16 {"
    "%0, %1, %2, %3, %4, %5, %6, %7, %8, %9, %10, %11, %12, %13, %14, %15, "
    "%16, %17, %18, %19, %20, %21, %22, %23, %24, %25, %26, %27, %28, %29, %30, %31, "
    "%32, %33, %34, %35, %36, %37, %38, %39, %40, %41, %42, %43, %44, %45, %46, %47, "
    "%48, %49, %50, %51, %52, %53, %54, %55, %56, %57, %58, %59, %60, %61, %62, %63, "
    "%64, %65, %66, %67, %68, %69, %70, %71, %72, %73, %74, %75, %76, %77, %78, %79, "
    "%80, %81, %82, %83, %84, %85, %86, %87, %88, %89, %90, %91, %92, %93, %94, %95, "
    "%96, %97, %98, %99, %100, %101, %102, %103, %104, %105, %106, %107, %108, %109, %110, %111, "
    "%112, %113, %114, %115, %116, %117, %118, %119, %120, %121, %122, %123, %124, %125, %126, %127"
    "}, %128, %129, p, 1, 1, 0, 1;\n}\n"
    : "+f"(d[0]), "+f"(d[1]), "+f"(d[2]), "+f"(d[3]), "+f"(d[4]), "+f"(d[5]), "+f"(d[6]), "+f"(d[7]),
      "+f"(d[8]), "+f"(d[9]), "+f"(d[10]), "+f"(d[11]), "+f"(d[12]), "+f"(d[13]), "+f"(d[14]), "+f"(d[15]),
      "+f"(d[16]), "+f"(d[17]), "+f"(d[18]), "+f"(d[19]), "+f"(d[20]), "+f"(d[21]), "+f"(d[22]), "+f"(d[23]),
      "+f"(d[24]), "+f"(d[25]), "+f"(d[26]), "+f"(d[27]), "+f"(d[28]), "+f"(d[29]), "+f"(d[30]), "+f"(d[31]),
      "+f"(d[32]), "+f"(d[33]), "+f"(d[34]), "+f"(d[35]), "+f"(d[36]), "+f"(d[37]), "+f"(d[38]), "+f"(d[39]),
      "+f"(d[40]), "+f"(d[41]), "+f"(d[42]), "+f"(d[43]), "+f"(d[44]), "+f"(d[45]), "+f"(d[46]), "+f"(d[47]),
      "+f"(d[48]), "+f"(d[49]), "+f"(d[50]), "+f"(d[51]), "+f"(d[52]), "+f"(d[53]), "+f"(d[54]), "+f"(d[55]),
      "+f"(d[56]), "+f"(d[57]), "+f"(d[58]), "+f"(d[59]), "+f"(d[60]), "+f"(d[61]), "+f"(d[62]), "+f"(d[63]),
      "+f"(d[64]), "+f"(d[65]), "+f"(d[66]), "+f"(d[67]), "+f"(d[68]), "+f"(d[69]), "+f"(d[70]), "+f"(d[71]),
      "+f"(d[72]), "+f"(d[73]), "+f"(d[74]), "+f"(d[75]), "+f"(d[76]), "+f"(d[77]), "+f"(d[78]), "+f"(d[79]),
      "+f"(d[80]), "+f"(d[81]), "+f"(d[82]), "+f"(d[83]), "+f"(d[84]), "+f"(d[85]), "+f"(d[86]), "+f"(d[87]),
      "+f"(d[88]), "+f"(d[89]), "+f"(d[90]), "+f"(d[91]), "+f"(d[92]), "+f"(d[93]), "+f"(d[94]), "+f"(d[95]),
      "+f"(d[96]), "+f"(d[97]), "+f"(d[98]), "+f"(d[99]), "+f"(d[100]), "+f"(d[101]), "+f"(d[102]), "+f"(d[103]),
      "+f"(d[104]), "+f"(d[105]), "+f"(d[106]), "+f"(d[107]), "+f"(d[108]), "+f"(d[109]), "+f"(d[110]), "+f"(d[111]),
      "+f"(d[112]), "+f"(d[113]), "+f"(d[114]), "+f"(d[115]), "+f"(d[116]), "+f"(d[117]), "+f"(d[118]), "+f"(d[119]),
      "+f"(d[120]), "+f"(d[121]), "+f"(d[122]), "+f"(d[123]), "+f"(d[124]), "+f"(d[125]), "+f"(d[126]), "+f"(d[127])
    : "l"(da), "l"(db), "r"(scale_d));
}
__device__ __forceinline__ void wgmma_rs_n256_t1(float (&d)[128], uint32_t a0, uint32_t a1, uint32_t a2, uint32_t a3, uint64_t db, int scale_d) {
  asm volatile(
    "{\n.reg .pred p;\nsetp.ne.b32 p, %133, 0;\n"
    "wgmma.mma_async.sync.aligned.m64n256k16.f32.bf16.bf16 {"
    "%0, %1, %2, %3, %4, %5, %6, %7, %8, %9, %10, %11, %12, %13, %14, %15, "
    "%16, %17, %18, %19, %20, %21, %22, %23, %24, %25, %26, %27, %28, %29, %30, %31, "
    "%32, %33, %34, %35, %36, %37, %38, %39, %40, %41, %42, %43, %44, %45, %46, %47, "
    "%48, %49, %50, %51, %52, %53, %54, %55, %56, %57, %58, %59, %60, %61, %62, %63, "
    "%64, %65, %66, %67, %68, %69, %70, %71, %72, %73, %74, %75, %76, %77, %78, %79, "
    "%80, %81, %82, %83, %84, %85, %86, %87, %88, %89, %90, %91, %92, %93, %94, %95, "
    "%96, %97, %98, %99, %100, %101, %102, %103, %104, %105, %106, %107, %108, %109, %110, %111, "
    "%112, %113, %114, %115, %116, %117, %118, %119, %120, %121, %122, %123, %124, %125, %126, %127"
    "}, {%128, %129, %130, %131}, %132, p, 1, 1, 1;\n}\n"
    : "+f"(d[0]), "+f"(d[1]), "+f"(d[2]), "+f"(d[3]), "+f"(d[4]), "+f"(d[5]), "+f"(d[6]), "+f"(d[7]),
      "+f"(d[8]), "+f"(d[9]), "+f"(d[10]), "+f"(d[11]), "+f"(d[12]), "+f"(d[13]), "+f"(d[14]), "+f"(d[15]),
      "+f"(d[16]), "+f"(d[17]), "+f"(d[18]), "+f"(d[19]), "+f"(d[20]), "+f"(d[21]), "+f"(d[22]), "+f"(d[23]),
      "+f"(d[24]), "+f"(d[25]), "+f"(d[26]), "+f"(d[27]), "+f"(d[28]), "+f"(d[29]), "+f"(d[30]), "+f"(d[31]),
      "+f"(d[32]), "+f"(d[33]), "+f"(d[34]), "+f"(d[35]), "+f"(d[36]), "+f"(d[37]), "+f"(d[38]), "+f"(d[39]),
      "+f"(d[40]), "+f"(d[41]), "+f"(d[42]), "+f"(d[43]), "+f"(d[44]), "+f"(d[45]), "+f"(d[46]), "+f"(d[47]),
      "+f"(d[48]), "+f"(d[49]), "+f"(d[50]), "+f"(d[51]), "+f"(d[52]), "+f"(d[53]), "+f"(d[54]), "+f"(d[55]),
      "+f"(d[56]), "+f"(d[57]), "+f"(d[58]), "+f"(d[59]), "+f"(d[60]), "+f"(d[61]), "+f"(d[62]), "+f"(d[63]),
      "+f"(d[64]), "+f"(d[65]), "+f"(d[66]), "+f"(d[67]), "+f"(d[68]), "+f"(d[69]), "+f"(d[70]), "+f"(d[71]),
      "+f"(d[72]), "+f"(d[73]), "+f"(d[74]), "+f"(d[75]), "+f"(d[76]), "+f"(d[77]), "+f"(d[78]), "+f"(d[79]),
      "+f"(d[80]), "+f"(d[81]), "+f"(d[82]), "+f"(d[83]), "+f"(d[84]), "+f"(d[85]), "+f"(d[86]), "+f"(d[87]),
      "+f"(d[88]), "+f"(d[89]), "+f"(d[90]), "+f"(d[91]), "+f"(d[92]), "+f"(d[93]), "+f"(d[94]), "+f"(d[95]),
      "+f"(d[96]), "+f"(d[97]), "+f"(d[98]), "+f"(d[99]), "+f"(d[100]), "+f"(d[101]), "+f"(d[102]), "+f"(d[103]),
      "+f"(d[104]), "+f"(d[105]), "+f"(d[106]), "+f"(d[107]), "+f"(d[108]), "+f"(d[109]), "+f"(d[110]), "+f"(d[111]),
      "+f"(d[112]), "+f"(d[113]), "+f"(d[114]), "+f"(d[115]), "+f"(d[116]), "+f"(d[117]), "+f"(d[118]), "+f"(d[119]),
      "+f"(d[120]), "+f"(d[121]), "+f"(d[122]), "+f"(d[123]), "+f"(d[124]), "+f"(d[125]), "+f"(d[126]), "+f"(d[127])
    : "r"(a0), "r"(a1), "r"(a2), "r"(a3), "l"(db), "r"(scale_d));
}
__device__ __forceinline__ void wgmma_ss_n96_t1(float (&d)[48], uint64_t da, uint64_t db, int scale_d) {
  asm volatile(
    "{\n.reg .pred p;\nsetp.ne.b32 p, %50, 0;\n"
    "wgmma.mma_async.sync.aligned.m64n96k16.f32.bf16.bf16 {"
    "%0, %1, %2, %3, %4, %5, %6, %7, %8, %9, %10, %11, %12, %13, %14, %15, "
    "%16, %17, %18, %19, %20, %21, %22, %23, %24, %25, %26, %27, %28, %29, %30, %31, "
    "%32, %33, %34, %35, %36, %37, %38, %39, %40, %41, %42, %43, %44, %45, %46, %47"
    "}, %48, %49, p, 1, 1, 0, 1;\n}\n"
    : "+f"(d[0]), "+f"(d[1]), "+f"(d[2]), "+f"(d[3]), "+f"(d[4]), "+f"(d[5]), "+f"(d[6]), "+f"(d[7]),
      "+f"(d[8]), "+f"(d[9]), "+f"(d[10]), "+f"(d[11]), "+f"(d[12]), "+f"(d[13]), "+f"(d[14]), "+f"(d[15]),
      "+f"(d[16]), "+f"(d[17]), "+f"(d[18]), "+f"(d[19]), "+f"(d[20]), "+f"(d[21]), "+f"(d[22]), "+f"(d[23]),
      "+f"(d[24]), "+f"(d[25]), "+f"(d[26]), "+f"(d[27]), "+f"(d[28]), "+f"(d[29]), "+f"(d[30]), "+f"(d[31]),
      "+f"(d[32]), "+f"(d[33]), "+f"(d[34]), "+f"(d[35]), "+f"(d[36]), "+f"(d[37]), "+f"(d[38]), "+f"(d[39]),
      "+f"(d[40]), "+f"(d[41]), "+f"(d[42]), "+f"(d[43]), "+f"(d[44]), "+f"(d[45]), "+f"(d[46]), "+f"(d[47])
    : "l"(da), "l"(db), "r"(scale_d));
}

#define TS(k)

constexpr int B_PP = 1;
constexpr int B_CONS = 3;
constexpr int B_WG = 4;
constexpr int B_AUX = 6;
constexpr int B_X = 7;

__global__ void __cluster_dims__(2, 1, 1) __launch_bounds__(384, 1)
fused_kernel(const __grid_constant__ Maps mp, const __nv_bfloat16* __restrict__ x, const __nv_bfloat16* __restrict__ kc,
             const __nv_bfloat16* __restrict__ wo, const __nv_bfloat16* __restrict__ wg, const __nv_bfloat16* __restrict__ wu,
             const __nv_bfloat16* __restrict__ wd, const __nv_bfloat16* __restrict__ cvec, const __nv_bfloat16* __restrict__ wmod,
             __nv_bfloat16* __restrict__ out) {
  extern __shared__ __align__(1024) uint8_t sm_raw[];
  const uint32_t sb = smem_u32(sm_raw);
  const int tid = threadIdx.x, lane = tid & 31;
  const int b = blockIdx.x;
  const uint32_t rank = b & 1;
  const int g = (b >> 1) & 7;
  const int rt = (b >> 4) * 2 + rank;
  auto FULL = [&](int h) { return sb + OFF_BAR + 8 * h; };
  auto EMPTY = [&](int h) { return sb + OFF_BAR + 112 + 8 * h; };
  auto AFULL = [&](int s) { return sb + OFF_BAR + 200 + 8 * s; };
  auto AEMPTY = [&](int s) { return sb + OFF_BAR + 232 + 8 * s; };
  auto XFULL = [&](int r) { return sb + OFF_BAR + 288 + 8 * r; };

  if (tid == 0) {
    trap_if(sb & 1023);
#pragma unroll 1
    for (int i = 0; i < 40; i++) mbar_init(sb + OFF_BAR + 8 * i, (i >= 14 && i < 28) || (i >= 32 && i < 36) ? 16 : 1);
    asm volatile("fence.mbarrier_init.release.cluster;" ::: "memory");
    fence_async_smem();
  }
  __syncwarp();
  asm volatile("barrier.cluster.arrive.relaxed.aligned;" ::: "memory");

  if (tid < 128) {
    asm volatile("setmaxnreg.dec.sync.aligned.u32 %0;" :: "n"(PROD_REGS));
    if (tid < 32) {
      if (lane < 4) mbar_expect_tx(XFULL(lane), SLOT);
      __syncwarp();
      tma_load(sb + (lane & 7) * HALF + (lane >> 3) * 4096, &mp.x, XFULL(lane >> 3), (lane & 7) * 64, rt * 128 + (lane >> 3) * 32);
    }
    asm volatile("barrier.cluster.wait.aligned;" ::: "memory");
    if (tid >= 64) {
      const int j = tid - 64;
      mbar_wait(AFULL(3), 0);
      float a[8];
#pragma unroll
      for (int i = 0; i < 8; i++) a[i] = 0.f;
#pragma unroll 1
      for (int k = j >> 1; k < 512; k += 32) {
        const uint4 w = ldg_nc128(wmod + (size_t)k * 3072 + 1024 + b * 16 + (j & 1) * 8);
        const float sc = silu_bf(__bfloat162float(cvec[k]));
        a[0] += sc * blo(w.x); a[1] += sc * bhi(w.x); a[2] += sc * blo(w.y); a[3] += sc * bhi(w.y);
        a[4] += sc * blo(w.z); a[5] += sc * bhi(w.z); a[6] += sc * blo(w.w); a[7] += sc * bhi(w.w);
      }
      const float r = xreduce8(a, lane);
      if ((lane & 2) == 0) sts32(sb + OFF_RED2 + ((j >> 5) * 16 + (lane & 1) * 8 + (lane >> 2)) * 4, __float_as_uint(r));
      bar_sync(B_AUX, 64);
      if (j < 8) {
        const float v0 = __uint_as_float(lds32(sb + OFF_RED2 + 8 * j)) + __uint_as_float(lds32(sb + OFF_RED2 + 64 + 8 * j));
        const float v1 = __uint_as_float(lds32(sb + OFF_RED2 + 8 * j + 4)) + __uint_as_float(lds32(sb + OFF_RED2 + 68 + 8 * j));
        uint32_t w = pack2(v0, v1);
        if ((b >> 5) == 2) w = one_plus(w);
        g_sync.late[(b >> 2) * 32 + (j & 3) * 8 + (b & 3) * 2 + (j >> 2)] = w;
        __syncwarp(0xffu);
        if (j == 0) asm volatile("red.release.gpu.global.add.u32 [%0], 1;" :: "l"(&g_sync.late_cnt) : "memory");
      }
    } else if (tid == 0) {
      uint32_t pe = 0x3f00;
      int h6 = 8, gi = 0, dj = 0;
#pragma unroll 1
      for (int i = 0; i < 110; i++) {
        if (i == 32) {
#pragma unroll 1
          for (int u = 0; u < 129; u++) {
            if (u == 127) continue;
            const int isv = u != 0 && (u & 1) == 0, t = isv ? (u >> 1) - 1 : (u + 1) >> 1;
            const int s = isv ? 4 - (t & 1) : 5 + (t & 1);
            if (t < 2) { mbar_wait(EMPTY(2 * s), (pe >> (2 * s)) & 1); mbar_wait(EMPTY(2 * s + 1), (pe >> (2 * s)) & 1); pe ^= 3u << (2 * s); }
            else mbar_wait(AEMPTY(s), ((t >> 1) & 1) ^ 1);
            mbar_expect_tx(AFULL(s), SLOT);
            tma_load_mc(sb + s * SLOT + rank * HALF, isv ? &mp.v : &mp.k, AFULL(s), rank * 64, g * SEQ + (t & 15) * 128);
          }
          h6 = 10;
        }
        const CUtensorMap* m; int h, xx, yy;
        if (i < 32) { m = &mp.wq; h = h6; xx = g * 512 + (i < 16 ? 256 : 0) + rank * 128; yy = (i & 15) * 32; }
        else if (i < 64) { m = &mp.wo; h = (0x7698dcba >> ((i & 7) * 4)) & 15; xx = ((i >> 4) & 1) * 256 + rank * 128; yy = g * 512 + (i & 15) * 32; }
        else if (gi < 32 && gi < 24 + 2 * dj) { m = rank ? &mp.wu : &mp.wg; h = h6; xx = g * FS + (gi >> 4) * 128; yy = (gi & 15) * 32; gi++; }
        else { m = &mp.wd; h = dj < 7 ? dj : dj < 13 ? h6 : 7; xx = (h >= 7 ? 256 : 0) + rank * 128; yy = g * FS + (h >= 7 ? h - 7 : h) * 32; dj++; }
        if (h == h6 && (i < 32 || i >= 64)) h6 = h6 == 13 ? 8 : h6 + 1;
        if ((i >> 3) == 4) mbar_wait(AEMPTY(h >> 1), 1);
        else { mbar_wait(EMPTY(h), (pe >> h) & 1); pe ^= 1u << h; }
        mbar_expect_tx(FULL(h), HALF);
        tma_load_mc(sb + h * HALF + rank * 8192, m, FULL(h), xx, yy);
        tma_load_mc(sb + h * HALF + rank * 8192 + 4096, m, FULL(h), xx + 64, yy);
      }
    } else if (tid >= 32) {
      if (lane < 8) tma_prefetch(&mp.wq, g * 512 + (rt < 8 ? 256 : 0) + (lane & 3) * 64, (rt & 7) * 64 + (lane >> 2) * 32);
      mbar_wait(EMPTY(8), 0);
      if (lane < 4) tma_prefetch((lane & 2) ? &mp.v : &mp.k, (lane & 1) * 64, g * SEQ + rt * 128);
      mbar_wait(AFULL(3), 0);
      if (lane < 4) bulk_prefetch((const uint8_t*)(lane == 0 ? wo : lane == 1 ? wg : lane == 2 ? wu : wd) + (size_t)b * (lane ? 14336 : 32768), lane ? 14336 : 32768);
      const uint32_t tag = lds32(sb + OFF_EPOCH);
      int n = 0;
      while ((int)(flag_get(&g_sync.late_cnt) - tag * 128) < 0) { __nanosleep(200); trap_if(++n > (1 << 22)); }
      fence_gpu();
#pragma unroll 1
      for (int phase = 0; phase < 3; phase++) {
        bar_sync(B_X, 288);
        if (lane < 8) mbar_expect_tx(FULL(lane), HALF);
        __syncwarp();
        bool done = lane >= 8;
        n = 0;
        while (!__all_sync(~0u, done)) {
          if (!done && flag_get(&g_sync.flag[(phase * 16 + rt) * 32 + lane]) == tag) {
            fence_gpu();
            asm volatile("fence.proxy.async.global;" ::: "memory");
            if (phase == 1) {
#pragma unroll 1
              for (int k = 0; k < 8; k++) tma_load(sb + k * HALF + lane * 2048, &mp.h2, FULL(k), k * 64, rt * 128 + lane * 16);
            } else {
              bulk_load(sb + lane * HALF, g_part + ((size_t)(rt * 8 + g) * 8 + lane) * 1024, HALF, FULL(lane));
            }
            done = true;
          }
          trap_if(++n > (1 << 24));
        }
      }
    }
  } else {
    asm volatile("setmaxnreg.inc.sync.aligned.u32 %0;" :: "n"(CONS_REGS));
    const int ct = tid - 128, cw = ct >> 7, wid = ct >> 5;
    uint32_t rel0;
    asm volatile("mapa.shared::cluster.u32 %0, %1, %2;" : "=r"(rel0) : "r"(EMPTY(0)), "r"(lane & 1));
    auto release = [&](int h) { if (lane < 2) asm volatile("mbarrier.arrive.shared::cluster.b64 _, [%0];" :: "r"(rel0 + 8 * h) : "memory"); };
    auto release_a = [&](int s) { release(15 + s); };
    uint32_t pf = 0;
    auto wait_full = [&](int h) { mbar_wait(FULL(h), (pf >> h) & 1); pf ^= 1u << h; };
    const uint32_t frag_row = wid * 16 + (lane & 15);
    auto frag_addr = [&](int slot, int kk) { return sb + slot * SLOT + (kk >> 2) * 16384 + frag_row * 128 + ((((kk & 3) * 2 + (lane >> 4)) ^ (lane & 7)) << 4); };
    uint32_t tag;
    TS(31);

    {
      asm volatile("ld.relaxed.gpu.global.u32 %0, [%1];" : "=r"(tag) : "l"(&g_sync.epoch) : "memory");
      const uint4 w0 = ldg_nc128(wmod + (size_t)ct * 3072 + b * 8), w1 = ldg_nc128(wmod + (size_t)(ct + 256) * 3072 + b * 8);
      const float c0 = __bfloat162float(cvec[ct]), c1 = __bfloat162float(cvec[ct + 256]);
      asm volatile("barrier.cluster.wait.aligned;" ::: "memory");
      tag += 1;
      if (ct == 0) sts32(sb + OFF_EPOCH, tag);
      {
        const float s0 = silu_bf(c0), s1 = silu_bf(c1);
        float a[8] = {s0 * blo(w0.x) + s1 * blo(w1.x), s0 * bhi(w0.x) + s1 * bhi(w1.x), s0 * blo(w0.y) + s1 * blo(w1.y), s0 * bhi(w0.y) + s1 * bhi(w1.y),
                      s0 * blo(w0.z) + s1 * blo(w1.z), s0 * bhi(w0.z) + s1 * bhi(w1.z), s0 * blo(w0.w) + s1 * blo(w1.w), s0 * bhi(w0.w) + s1 * bhi(w1.w)};
        float r = xreduce8(a, lane);
        r += __shfl_xor_sync(~0u, r, 1);
        if ((lane & 3) == 0) sts32(sb + OFF_RED + ((lane >> 2) * 8 + wid) * 4, __float_as_uint(r));
        bar_sync(B_CONS, 256);
        if (ct < 8) {
          const uint4 u = lds128(sb + OFF_RED + ct * 32), w = lds128(sb + OFF_RED + ct * 32 + 16);
          const float v0 = ((__uint_as_float(u.x) + __uint_as_float(u.y)) + (__uint_as_float(u.z) + __uint_as_float(u.w))) + ((__uint_as_float(w.x) + __uint_as_float(w.y)) + (__uint_as_float(w.z) + __uint_as_float(w.w)));
          const float v1 = __shfl_xor_sync(0xffu, v0, 1);
          if ((ct & 1) == 0) st_ll(&g_sync.modll[b * 4 + (ct >> 1)], pack2(v0, v1), tag);
        }
      }
      TS(0);
      mbar_wait(XFULL(wid >> 1), 0);
      TS(19);
      uint32_t nm, rh, rl;
      {
        float su[4] = {0.f, 0.f, 0.f, 0.f}, d0[4] = {0.f, 0.f, 0.f, 0.f}, d1[4] = {0.f, 0.f, 0.f, 0.f};
#pragma unroll 1
        for (int sl = 0; sl < 8; sl++) {
#pragma unroll
          for (int kk = 0; kk < 4; kk++) {
            uint32_t a0, a1, a2, a3;
            ldsm4(frag_addr(0, kk) + sl * HALF, a0, a1, a2, a3);
            mma16816(su[0], su[1], su[2], su[3], a0, a1, a2, a3, 0x3f803f80u, 0x3f803f80u);
            mma16816(d0[0], d0[1], d0[2], d0[3], a0, a1, a2, a3, a0, a2);
            mma16816(d1[0], d1[1], d1[2], d1[3], a0, a1, a2, a3, a1, a3);
          }
        }
        const bool odd = lane & 4;
        const int src = (lane & 7) * 4 + ((lane & 7) >> 1);
        const float qa = __shfl_sync(~0u, odd ? d0[1] : d0[0], src), qb = __shfl_sync(~0u, odd ? d1[3] : d1[2], src);
        const float sa = __shfl_sync(~0u, su[0], src), sc = __shfl_sync(~0u, su[2], src);
        const float mean = ((lane & 8) ? sc : sa) * (1.f / DM);
        const float r = ln_rstd(mean, ((lane & 8) ? qb : qa) * (1.f / DM));
        nm = pack2(-mean, -mean); rh = pack2(r, r);
        const float lo = r - blo(rh);
        rl = pack2(lo, lo);
      }
      TS(1);
      {
        const int c = ct & 127;
        unsigned long long pk[4];
        int n = 0;
        while (true) {
#pragma unroll
          for (int i = 0; i < 4; i++) pk[i] = ld_ll(&g_sync.modll[i * 128 + c]);
          if ((((uint32_t)(pk[0] >> 32) ^ tag) | ((uint32_t)(pk[1] >> 32) ^ tag) | ((uint32_t)(pk[2] >> 32) ^ tag) | ((uint32_t)(pk[3] >> 32) ^ tag)) == 0) break;
          trap_if(++n > (1 << 24));
        }
#pragma unroll
        for (int i = 0; i < 4; i++) sts32(sb + OFF_MODSM + (i * 128 + c) * 4, i < 2 ? (uint32_t)pk[i] : one_plus((uint32_t)pk[i]));
      }
      bar_sync(B_WG + cw, 128);
      TS(2);
#pragma unroll 1
      for (int i = 0; i < 16; i++) {
#pragma unroll
        for (int c = 0; c < 2; c++) {
          const int ch = (lane >> 4) * 4 + (i & 1) * 2 + c;
          const uint32_t ad = sb + (i >> 1) * HALF + frag_row * 128 + ((ch ^ (lane & 7)) << 4);
          const uint32_t md = sb + OFF_MODSM + (i >> 1) * 128 + ch * 16;
          uint4 u = lds128(ad);
          const uint4 sv = lds128(md), gv = lds128(md + 1024);
          auto nrm = [&](uint32_t xv, uint32_t gw, uint32_t sw) { const uint32_t d = hfma2(xv, 0x3f803f80u, nm); return hfma2(hfma2(d, rh, hfma2(d, rl, 0x80008000u)), gw, sw); };
          u.x = nrm(u.x, gv.x, sv.x); u.y = nrm(u.y, gv.y, sv.y); u.z = nrm(u.z, gv.z, sv.z); u.w = nrm(u.w, gv.w, sv.w);
          sts128(ad, u.x, u.y, u.z, u.w);
        }
      }
      fence_async_smem();
      bar_sync(B_WG + cw, 128);
    }
    TS(3);

    const uint64_t dA0 = make_desc(sb + cw * 8192, 16, 1024);
    const uint64_t dB0 = make_desc(sb, 4096, 1024);
    uint32_t q[32];

    {
      uint32_t held[64];
      float acc[128];
      int h6 = 8, prev = 8;
#pragma unroll 1
      for (int pass = 0; pass < 2; pass++) {
#pragma unroll 1
        for (int k = 0; k < 16; k++) {
          wait_full(h6);
          wg_fence();
#pragma unroll
          for (int ks = 0; ks < 2; ks++) wgmma_ss_n256_t1(acc, dA0 + (k >> 1) * 1024 + (k & 1) * 4 + ks * 2, dB0 + h6 * 1024 + ks * 128, (k | ks) != 0);
          wg_commit();
          if (k > 0) { wg_wait<1>(); release(prev); }
          prev = h6; h6 = h6 == 13 ? 8 : h6 + 1;
        }
        wg_wait<0>(); pin(acc);
        release(prev);
        if (pass == 0) {
#pragma unroll
          for (int j = 0; j < 64; j++) held[j] = pack2(acc[2 * j], acc[2 * j + 1]);
          pin(held);
        }
      }
      release(6); release(7);
#pragma unroll
      for (int j = 0; j < 32; j++) q[j] = pack2(acc[2 * j], acc[2 * j + 1]);
#pragma unroll
      for (int kk = 0; kk < 8; kk++) {
        stsm4(frag_addr(0, kk), pack2(acc[64 + 8 * kk], acc[65 + 8 * kk]), pack2(acc[66 + 8 * kk], acc[67 + 8 * kk]), pack2(acc[68 + 8 * kk], acc[69 + 8 * kk]), pack2(acc[70 + 8 * kk], acc[71 + 8 * kk]));
        stsm4(frag_addr(1, kk), held[4 * kk], held[4 * kk + 1], held[4 * kk + 2], held[4 * kk + 3]);
        stsm4(frag_addr(2, kk), held[32 + 4 * kk], held[33 + 4 * kk], held[34 + 4 * kk], held[35 + 4 * kk]);
      }
      pin(q);
    }
    TS(4);

    {
      const float cl2 = 0.08838834764831845f * 1.4426950408889634f;
      const uint64_t dK0 = make_desc(sb + 5 * SLOT, 16, 1024);
      const uint64_t dV0 = make_desc(sb + 3 * SLOT, 16384, 1024);
      float o[64], s[64];
      uint32_t p[32];
      float ms0 = 0.f, ms1 = 0.f, l0 = 1.f, l1 = 1.f, t0, t1;
      auto qk = [&](int st) {
#pragma unroll
        for (int kk = 0; kk < 8; kk++) wgmma_rs_n128_t0(s, q[4 * kk], q[4 * kk + 1], q[4 * kk + 2], q[4 * kk + 3], dK0 + st * 2048 + (kk >> 2) * 1024 + (kk & 3) * 2, kk != 0);
        wg_commit();
      };
      auto pv = [&](int st, int acc) {
#pragma unroll
        for (int kk = 0; kk < 8; kk++) wgmma_rs_n128_t1(o, p[4 * kk], p[4 * kk + 1], p[4 * kk + 2], p[4 * kk + 3], dV0 + st * 2048 + kk * 128, (kk != 0) | acc);
        wg_commit();
      };
      auto rowmax = [&](float& a, float& c) {
        float u[4], w[4];
#pragma unroll
        for (int j = 0; j < 4; j++) { u[j] = fmaxf(s[4 * j], s[4 * j + 1]); w[j] = fmaxf(s[4 * j + 2], s[4 * j + 3]); }
#pragma unroll
        for (int j = 4; j < 16; j++) { u[j & 3] = fmaxf(fmaxf(u[j & 3], s[4 * j]), s[4 * j + 1]); w[j & 3] = fmaxf(fmaxf(w[j & 3], s[4 * j + 2]), s[4 * j + 3]); }
        float x0 = fmaxf(fmaxf(u[0], u[1]), fmaxf(u[2], u[3])), x1 = fmaxf(fmaxf(w[0], w[1]), fmaxf(w[2], w[3]));
        x0 = fmaxf(x0, __shfl_xor_sync(~0u, x0, 1)); x1 = fmaxf(x1, __shfl_xor_sync(~0u, x1, 1));
        x0 = fmaxf(x0, __shfl_xor_sync(~0u, x0, 2)); x1 = fmaxf(x1, __shfl_xor_sync(~0u, x1, 2));
        a = x0 * cl2; c = x1 * cl2;
      };
      auto exprange = [&](auto j0, auto j1) {
#pragma unroll
        for (int j = j0; j < j1; j++) {
          s[4 * j] = ex2(fmaf(s[4 * j], cl2, -ms0)); s[4 * j + 1] = ex2(fmaf(s[4 * j + 1], cl2, -ms0));
          s[4 * j + 2] = ex2(fmaf(s[4 * j + 2], cl2, -ms1)); s[4 * j + 3] = ex2(fmaf(s[4 * j + 3], cl2, -ms1));
          if (j == 0) { t0 = s[0] + s[1]; t1 = s[2] + s[3]; } else { t0 += s[4 * j] + s[4 * j + 1]; t1 += s[4 * j + 2] + s[4 * j + 3]; }
        }
      };
      auto cvtp = [&]() {
#pragma unroll
        for (int j = 0; j < 32; j++) p[j] = pack2(s[2 * j], s[2 * j + 1]);
      };
      auto inv_l = [&](float& i0, float& i1) {
        float a = l0 + __shfl_xor_sync(~0u, l0, 1), c = l1 + __shfl_xor_sync(~0u, l1, 1);
        a += __shfl_xor_sync(~0u, a, 2); c += __shfl_xor_sync(~0u, c, 2);
        i0 = rcp_fast(a); i1 = rcp_fast(c);
      };
      if (cw == 0) bar_arrive(B_PP, 256);
      mbar_wait(AFULL(5), 0);
      float i0, i1;
#pragma unroll 1
      for (int t = 0; t < 64; t++) {
        const int st = t & 1;
        bar_sync(B_PP + cw, 256);
        wg_fence();
        qk(st);
        if (t > 0) mbar_wait(AFULL(3 + st), ((t - 1) >> 1) & 1);
        wg_fence();
        pv(st, (t & 15) != 1);
        bar_arrive(B_PP + (cw ^ 1), 256);
        const bool first = (t & 15) == 0;
        if (first) inv_l(i0, i1);
        wg_wait<1>(); pin(s);
        release_a(5 + st);
        if (first) { rowmax(ms0, ms1); l0 = 0.f; l1 = 0.f; }
        exprange(IC<0>(), IC<EXP_SPLIT>());
        pin(s);
        mbar_wait(AFULL(6 - st), ((t + 1 - (t == 63 ? 2 : 0)) >> 1) & 1);
        wg_wait<0>(); pin(o); pin(p);
        if (t > 0) release_a(3 + st);
        exprange(IC<EXP_SPLIT>(), IC<16>());
        if (first && t > 0) {
          const int slot = (t >> 4) - 1;
#pragma unroll
          for (int j = 0; j < 16; j++) { p[2 * j] = pack2(o[4 * j] * i0, o[4 * j + 1] * i0); p[2 * j + 1] = pack2(o[4 * j + 2] * i1, o[4 * j + 3] * i1); }
#pragma unroll
          for (int kk = 0; kk < 8; kk++) stsm4(frag_addr(slot, kk), p[4 * kk], p[4 * kk + 1], p[4 * kk + 2], p[4 * kk + 3]);
          fence_async_smem();
        }
        cvtp();
        if (__any_sync(~0u, !(t0 + t1 <= 1.2089258e24f))) {
          float4 sr[16];
          uint2 pr[16];
          const uint32_t* kp = (const uint32_t*)(kc + (size_t)(g * SEQ + (t & 15) * 128 + (lane >> 2)) * DH) + (lane & 3);
          float x0 = ms0, x1 = ms1;
#pragma unroll 1
          for (int j = 0; j < 16; j++) {
            float4 c = {0.f, 0.f, 0.f, 0.f};
#pragma unroll
            for (int kk = 0; kk < 8; kk++)
              mma16816(c.x, c.y, c.z, c.w, q[4 * kk], q[4 * kk + 1], q[4 * kk + 2], q[4 * kk + 3], ldg_nc32(kp + j * 512 + kk * 8), ldg_nc32(kp + j * 512 + kk * 8 + 4));
            sr[j] = c;
            x0 = fmaxf(x0, fmaxf(c.x, c.y) * cl2); x1 = fmaxf(x1, fmaxf(c.z, c.w) * cl2);
          }
          x0 = fmaxf(x0, __shfl_xor_sync(~0u, x0, 1)); x1 = fmaxf(x1, __shfl_xor_sync(~0u, x1, 1));
          x0 = fmaxf(x0, __shfl_xor_sync(~0u, x0, 2)); x1 = fmaxf(x1, __shfl_xor_sync(~0u, x1, 2));
          const float a0 = ex2(ms0 - x0), a1 = ex2(ms1 - x1);
          ms0 = x0; ms1 = x1; l0 *= a0; l1 *= a1; t0 = 0.f; t1 = 0.f;
#pragma unroll 1
          for (int j = 0; j < 16; j++) {
            const float4 c = sr[j];
            const float e0 = ex2(fmaf(c.x, cl2, -x0)), e1 = ex2(fmaf(c.y, cl2, -x0)), e2 = ex2(fmaf(c.z, cl2, -x1)), e3 = ex2(fmaf(c.w, cl2, -x1));
            t0 += e0 + e1; t1 += e2 + e3;
            pr[j] = make_uint2(pack2(e0, e1), pack2(e2, e3));
          }
#pragma unroll
          for (int j = 0; j < 16; j++) { o[4 * j] *= a0; o[4 * j + 1] *= a0; o[4 * j + 2] *= a1; o[4 * j + 3] *= a1; p[2 * j] = pr[j].x; p[2 * j + 1] = pr[j].y; }
        }
        l0 += t0; l1 += t1;
        if ((t & 15) == 15 && t < 63) {
#pragma unroll
          for (int kk = 0; kk < 8; kk++) ldsm4(frag_addr(t >> 4, kk), q[4 * kk], q[4 * kk + 1], q[4 * kk + 2], q[4 * kk + 3]);
        }
        pin(p); pin(o); pin(q);
        asm volatile("" : "+f"(l0), "+f"(l1) :: "memory");
      }
      mbar_wait(AFULL(3), 1);
      if (cw == 0) bar_sync(B_PP, 256);
      wg_fence();
      pv(0, 1);
      inv_l(i0, i1);
      wg_wait<0>(); pin(o);
      release_a(3);
#pragma unroll
      for (int j = 0; j < 16; j++) { q[2 * j] = pack2(o[4 * j] * i0, o[4 * j + 1] * i0); q[2 * j + 1] = pack2(o[4 * j + 2] * i1, o[4 * j + 3] * i1); }
      pin(q);
    }
    TS(10);

    uint4* const part_w = g_part + ((size_t)(rt * 8 + wid) * 8 + g) * 1024 + lane;
    auto store_part = [&](const float (&acc)[128], int pass) {
#pragma unroll
      for (int c = 0; c < 16; c++)
        stg128(part_w + (pass * 16 + c) * 32, pack2(acc[8 * c], acc[8 * c + 1]), pack2(acc[8 * c + 2], acc[8 * c + 3]), pack2(acc[8 * c + 4], acc[8 * c + 5]), pack2(acc[8 * c + 6], acc[8 * c + 7]));
    };
    auto publish = [&](int phase) {
      bar_sync(B_CONS, 256);
      if (ct == 0) flag_set(&g_sync.flag[(phase * 16 + rt) * 32 + g], tag);
    };
    auto gather = [&](float (&y)[32]) {
#pragma unroll
      for (int i = 0; i < 32; i++) y[i] = 0.f;
#pragma unroll 1
      for (int sg = 0; sg < 8; sg++) {
        wait_full(sg);
#pragma unroll
        for (int c = 0; c < 4; c++) {
          const uint4 w = lds128(sb + sg * HALF + wid * 2048 + c * 512 + lane * 16);
          y[8 * c] += blo(w.x); y[8 * c + 1] += bhi(w.x); y[8 * c + 2] += blo(w.y); y[8 * c + 3] += bhi(w.y);
          y[8 * c + 4] += blo(w.z); y[8 * c + 5] += bhi(w.z); y[8 * c + 6] += blo(w.w); y[8 * c + 7] += bhi(w.w);
        }
      }
    };
    auto late_vec = [&](uint32_t (&r)[8], int which) {
      const uint4 u = ldg_cg128(&g_sync.late[which * 256 + wid * 32 + (lane & 3) * 8]), w = ldg_cg128(&g_sync.late[which * 256 + wid * 32 + (lane & 3) * 8 + 4]);
      r[0] = u.x; r[1] = u.y; r[2] = u.z; r[3] = u.w; r[4] = w.x; r[5] = w.y; r[6] = w.z; r[7] = w.w;
    };
    auto write_rows = [&](const uint32_t (&w)[16], __nv_bfloat16* dst) {
      const uint32_t st = sb + wid * 2048;
      __syncwarp();
#pragma unroll
      for (int c = 0; c < 4; c++) stsm4(st + (lane & 15) * 128 + (((c * 2 + (lane >> 4)) ^ (lane & 7)) << 4), w[4 * c], w[4 * c + 1], w[4 * c + 2], w[4 * c + 3]);
      __syncwarp();
#pragma unroll
      for (int i = 0; i < 4; i++) {
        const int r = i * 4 + (lane >> 3);
        const uint4 u = lds128(st + r * 128 + (((lane & 7) ^ (r & 7)) << 4));
        stg128(dst + (size_t)(rt * 128 + g * 16 + r) * DM + wid * 64 + (lane & 7) * 8, u.x, u.y, u.z, u.w);
      }
    };
    const int mcol = wid * 32 + (lane & 3);

    {
      float acc[128];
#pragma unroll 1
      for (int pass = 0; pass < 2; pass++) {
        int prev = 0;
#pragma unroll 1
        for (int k = 0; k < 12; k++) {
          const int h = (0x7698dcba >> ((k & 7) * 4)) & 15;
          wait_full(h);
          wg_fence();
#pragma unroll
          for (int ks = 0; ks < 2; ks++) wgmma_ss_n256_t1(acc, dA0 + (k >> 1) * 1024 + (k & 1) * 4 + ks * 2, dB0 + h * 1024 + ks * 128, (k | ks) != 0);
          wg_commit();
          if (k > 0) { wg_wait<1>(); release(prev); }
          prev = h;
        }
#pragma unroll
        for (int k = 0; k < 4; k++) {
          const int h = k < 2 ? 8 + k : 4 + k;
          wait_full(h);
          wg_fence();
#pragma unroll
          for (int ks = 0; ks < 2; ks++) wgmma_rs_n256_t1(acc, q[8 * k + 4 * ks], q[8 * k + 4 * ks + 1], q[8 * k + 4 * ks + 2], q[8 * k + 4 * ks + 3], dB0 + h * 1024 + ks * 128, 1);
          wg_commit();
          wg_wait<1>();
          if (k < 3 || pass == 0) release(k == 0 ? 13 : k == 1 ? 8 : k == 2 ? 9 : 6);
        }
        wg_wait<0>(); pin(acc); pin(q);
        if (pass == 0) release(7); else bar_arrive(B_X, 288);
        store_part(acc, pass);
      }
    }
    publish(0);
    TS(11);

    uint32_t x1[16];
    {
      uint32_t ga[8], cb[8], sbv[8];
      const uint32_t* xp = (const uint32_t*)(x + (size_t)(rt * 128 + g * 16 + (lane >> 2)) * DM) + mcol;
#pragma unroll
      for (int j = 0; j < 8; j++) { x1[2 * j] = ldg_nc32(xp + 4 * j); x1[2 * j + 1] = ldg_nc32(xp + 8 * (DM / 2) + 4 * j); }
      mbar_wait(FULL(0), pf & 1);
      late_vec(ga, 0); late_vec(sbv, 1); late_vec(cb, 2);
      float y[32];
      gather(y);
      TS(12);
      float s0 = 0.f, q0 = 0.f, s1 = 0.f, q1 = 0.f;
#pragma unroll
      for (int j = 0; j < 8; j++) {
        y[4 * j] = fmaf(blo(ga[j]), y[4 * j], blo(x1[2 * j])); y[4 * j + 1] = fmaf(bhi(ga[j]), y[4 * j + 1], bhi(x1[2 * j]));
        y[4 * j + 2] = fmaf(blo(ga[j]), y[4 * j + 2], blo(x1[2 * j + 1])); y[4 * j + 3] = fmaf(bhi(ga[j]), y[4 * j + 3], bhi(x1[2 * j + 1]));
        x1[2 * j] = pack2(y[4 * j], y[4 * j + 1]); x1[2 * j + 1] = pack2(y[4 * j + 2], y[4 * j + 3]);
        s0 += y[4 * j] + y[4 * j + 1]; q0 = fmaf(y[4 * j], y[4 * j], q0); q0 = fmaf(y[4 * j + 1], y[4 * j + 1], q0);
        s1 += y[4 * j + 2] + y[4 * j + 3]; q1 = fmaf(y[4 * j + 2], y[4 * j + 2], q1); q1 = fmaf(y[4 * j + 3], y[4 * j + 3], q1);
      }
#pragma unroll
      for (int o = 1; o < 4; o <<= 1) { s0 += __shfl_xor_sync(~0u, s0, o); q0 += __shfl_xor_sync(~0u, q0, o); s1 += __shfl_xor_sync(~0u, s1, o); q1 += __shfl_xor_sync(~0u, q1, o); }
      if ((lane & 3) == 0) sts128(sb + OFF_MODSM + (wid * 8 + (lane >> 2)) * 16, __float_as_uint(s0), __float_as_uint(q0), __float_as_uint(s1), __float_as_uint(q1));
      bar_sync(B_CONS, 256);
      s0 = q0 = s1 = q1 = 0.f;
#pragma unroll 2
      for (int w = 0; w < 8; w++) { const uint4 u = lds128(sb + OFF_MODSM + (w * 8 + (lane >> 2)) * 16); s0 += __uint_as_float(u.x); q0 += __uint_as_float(u.y); s1 += __uint_as_float(u.z); q1 += __uint_as_float(u.w); }
      const float m0 = s0 * (1.f / DM), m1 = s1 * (1.f / DM);
      const float r0 = ln_rstd(m0, q0 * (1.f / DM)), r1 = ln_rstd(m1, q1 * (1.f / DM));
      const float n0 = -bround(m0) * r0, n1 = -bround(m1) * r1;
      uint32_t hw[16];
#pragma unroll
      for (int j = 0; j < 8; j++) {
        hw[2 * j] = hfma2(pack2(fmaf(y[4 * j], r0, n0), fmaf(y[4 * j + 1], r0, n0)), cb[j], sbv[j]);
        hw[2 * j + 1] = hfma2(pack2(fmaf(y[4 * j + 2], r1, n1), fmaf(y[4 * j + 3], r1, n1)), cb[j], sbv[j]);
      }
      write_rows(hw, g_h2);
      bar_arrive(B_X, 288);
      publish(1);
      pin(x1);
    }
    TS(13);

    {
      uint32_t act[56];
      int h6 = 10, prev = 10;
      auto swiglu = [&](float gt0, float gt1, float up0, float up1) {
        const float h0 = 0.5f * gt0, h1 = 0.5f * gt1;
        return pack2(fmaf(h0, tanh_fast(h0), h0) * up0, fmaf(h1, tanh_fast(h1), h1) * up1);
      };
      {
        float acc[128];
#pragma unroll 1
        for (int k = 0; k < 16; k++) {
          if ((k & 1) == 0) wait_full(k >> 1);
          wait_full(h6);
          wg_fence();
#pragma unroll
          for (int ks = 0; ks < 2; ks++) wgmma_ss_n256_t1(acc, dA0 + (k >> 1) * 1024 + (k & 1) * 4 + ks * 2, dB0 + h6 * 1024 + ks * 128, (k | ks) != 0);
          wg_commit();
          if (k > 0) { wg_wait<1>(); release(prev); }
          prev = h6; h6 = h6 == 13 ? 8 : h6 + 1;
          if (k == 0) TS(14);
        }
        wg_wait<0>(); pin(acc);
        release(prev);
        TS(20);
#pragma unroll
        for (int j = 0; j < 32; j++) act[j] = swiglu(acc[2 * j], acc[2 * j + 1], acc[64 + 2 * j], acc[65 + 2 * j]);
      }
      {
        float ag[48], au[48];
#pragma unroll 1
        for (int k = 0; k < 16; k++) {
          wait_full(h6);
          wg_fence();
#pragma unroll
          for (int ks = 0; ks < 2; ks++) {
            wgmma_ss_n96_t1(ag, dA0 + (k >> 1) * 1024 + (k & 1) * 4 + ks * 2, dB0 + h6 * 1024 + ks * 128, (k | ks) != 0);
            wgmma_ss_n96_t1(au, dA0 + (k >> 1) * 1024 + (k & 1) * 4 + ks * 2, dB0 + h6 * 1024 + 512 + ks * 128, (k | ks) != 0);
          }
          wg_commit();
          if (k > 0) { wg_wait<1>(); release(prev); if ((k & 1) == 0) release((k >> 1) - 1); }
          prev = h6; h6 = h6 == 13 ? 8 : h6 + 1;
        }
        wg_wait<0>(); pin(ag); pin(au);
        release(prev); release(7);
        TS(21);
#pragma unroll
        for (int j = 0; j < 24; j++) act[32 + j] = swiglu(ag[2 * j], ag[2 * j + 1], au[2 * j], au[2 * j + 1]);
      }
      pin(act);
      TS(15);
      float acc[128];
#pragma unroll 1
      for (int pass = 0; pass < 2; pass++) {
#pragma unroll 1
        for (int k = 0; k < 7; k++) wait_full(pass * 7 + k);
        wg_fence();
#pragma unroll
        for (int ks = 0; ks < 14; ks++) wgmma_rs_n256_t1(acc, act[4 * ks], act[4 * ks + 1], act[4 * ks + 2], act[4 * ks + 3], dB0 + pass * 7168 + (ks >> 1) * 1024 + (ks & 1) * 128, ks != 0);
        wg_commit();
        wg_wait<0>(); pin(acc); pin(act);
        if (pass == 1) bar_arrive(B_X, 288);
        store_part(acc, pass);
      }
    }
    publish(2);
    asm volatile("barrier.cluster.arrive.relaxed.aligned;" ::: "memory");
    TS(16);

    {
      uint32_t gb[8];
      late_vec(gb, 3);
      float y[32];
      gather(y);
      TS(17);
      if (b == 0 && ct == 0) g_sync.epoch = tag;
      uint32_t ow[16];
#pragma unroll
      for (int j = 0; j < 8; j++) {
        ow[2 * j] = pack2(fmaf(blo(gb[j]), y[4 * j], blo(x1[2 * j])), fmaf(bhi(gb[j]), y[4 * j + 1], bhi(x1[2 * j])));
        ow[2 * j + 1] = pack2(fmaf(blo(gb[j]), y[4 * j + 2], blo(x1[2 * j + 1])), fmaf(bhi(gb[j]), y[4 * j + 3], bhi(x1[2 * j + 1])));
      }
      write_rows(ow, out);
    }
    TS(18);
    asm volatile("barrier.cluster.wait.aligned;" ::: "memory");
  }
}

typedef CUresult (*EncodeFn)(CUtensorMap*, CUtensorMapDataType, cuuint32_t, void*, const cuuint64_t*, const cuuint64_t*, const cuuint32_t*, const cuuint32_t*,
                             CUtensorMapInterleave, CUtensorMapSwizzle, CUtensorMapL2promotion, CUtensorMapFloatOOBfill);

void make_map(EncodeFn fn, CUtensorMap* m, const void* p, uint64_t rows, uint64_t cols, uint32_t box_rows) {
  cuuint64_t dims[2] = {cols, rows};
  cuuint64_t strides[1] = {cols * 2};
  cuuint32_t box[2] = {64, box_rows};
  cuuint32_t es[2] = {1, 1};
  fn(m, CU_TENSOR_MAP_DATA_TYPE_BFLOAT16, 2, const_cast<void*>(p), dims, strides, box, es, CU_TENSOR_MAP_INTERLEAVE_NONE, CU_TENSOR_MAP_SWIZZLE_128B,
     CU_TENSOR_MAP_L2_PROMOTION_L2_128B, CU_TENSOR_MAP_FLOAT_OOB_FILL_NONE);
}

}

extern "C" void kernel_launch(void* const* d_in, const int* in_sizes, int n_in, void* d_out, int out_size) {
  (void)in_sizes; (void)n_in; (void)out_size;
  typedef const __nv_bfloat16* P;
  P x = (P)d_in[0], k = (P)d_in[1], v = (P)d_in[2], wq = (P)d_in[3], wo = (P)d_in[4];
  P wg = (P)d_in[6], wu = (P)d_in[7], wd = (P)d_in[8], c = (P)d_in[9], wmod = (P)d_in[10];
  static EncodeFn fn = nullptr;
  static void* h2p = nullptr;
  if (!fn) {
    void* p = nullptr;
    cudaDriverEntryPointQueryResult qr;
    cudaGetDriverEntryPoint("cuTensorMapEncodeTiled", &p, cudaEnableDefault, &qr);
    fn = (EncodeFn)p;
    cudaGetSymbolAddress(&h2p, g_h2);
    cudaFuncSetAttribute(fused_kernel, cudaFuncAttributeMaxDynamicSharedMemorySize, SMEM_BYTES);
  }
  Maps mp;
  make_map(fn, &mp.wq, wq, 512, 4096, 32);
  make_map(fn, &mp.k, k, 8 * SEQ, DH, 128);
  make_map(fn, &mp.v, v, 8 * SEQ, DH, 128);
  make_map(fn, &mp.wo, wo, 4096, DM, 32);
  make_map(fn, &mp.wg, wg, DM, FF, 32);
  make_map(fn, &mp.wu, wu, DM, FF, 32);
  make_map(fn, &mp.wd, wd, FF, DM, 32);
  make_map(fn, &mp.h2, h2p, SEQ, DM, 16);
  make_map(fn, &mp.x, x, SEQ, DM, 32);
  fused_kernel<<<128, 384, SMEM_BYTES>>>(mp, x, k, wo, wg, wu, wd, c, wmod, (__nv_bfloat16*)d_out);
}
```

```cpp
#include <cuda_runtime.h>
#include <cuda_bf16.h>
#include <cuda.h>
#include <stdint.h>

namespace {

constexpr int SEQ = 2048, DM = 512, DH = 128, FF = 1792, FS = 224;
constexpr int SLOT = 32768, HALF = 16384;
constexpr int OFF_BAR = 7 * SLOT;
constexpr int OFF_MODSM = OFF_BAR + 320;
constexpr int OFF_RED = OFF_MODSM + 2048;
constexpr int OFF_RED2 = OFF_RED + 256;
constexpr int OFF_EPOCH = OFF_RED2 + 192;
constexpr int SMEM_BYTES = 232448;
static_assert(OFF_EPOCH + 16 <= SMEM_BYTES, "smem");

constexpr int CONS_REGS = 232, PROD_REGS = 40;
#define NORM_AHEAD 2
#define EXP_SPLIT 11

__device__ uint4 g_part[16 * 8 * 8 * 1024];
__device__ __nv_bfloat16 g_h2[SEQ * DM];
struct __align__(128) Sync {
  unsigned long long modll[512];
  unsigned int late[1024];
  unsigned int flag[3 * 16 * 32];
  unsigned int late_cnt;
  unsigned int pad[31];
  unsigned int epoch;
};
__device__ Sync g_sync;

struct Maps { CUtensorMap wq, k, v, wo, gu, wd, h2, x; };

__device__ __forceinline__ uint32_t smem_u32(const void* p) { return (uint32_t)__cvta_generic_to_shared(p); }
__device__ __forceinline__ void mbar_init(uint32_t bar, uint32_t cnt) { asm volatile("mbarrier.init.shared::cta.b64 [%0], %1;" :: "r"(bar), "r"(cnt) : "memory"); }
__device__ __forceinline__ void mbar_expect_tx(uint32_t bar, uint32_t bytes) { asm volatile("mbarrier.arrive.expect_tx.shared::cta.b64 _, [%0], %1;" :: "r"(bar), "r"(bytes) : "memory"); }
__device__ __forceinline__ void mbar_wait(uint32_t bar, uint32_t par) {
  asm volatile(
    "{\n.reg .pred p;\n.reg .u32 n;\n"
    "mov.u32 n, 0;\n"
    "W_LOOP:\n"
    "mbarrier.try_wait.parity.shared::cta.b64 p, [%0], %1;\n"
    "@p bra W_DONE;\n"
    "add.u32 n, n, 1;\n"
    "setp.lt.u32 p, n, 0x1000000;\n"
    "@p bra W_LOOP;\n"
    "trap;\n"
    "W_DONE:\n}" :: "r"(bar), "r"(par) : "memory");
}
__device__ __forceinline__ void mbar_wait_hot(uint32_t bar, uint32_t par) {
  asm volatile(
    "{\n.reg .pred p;\n.reg .u32 n;\n"
    "mbarrier.try_wait.parity.shared::cta.b64 p, [%0], %1;\n"
    "@p bra W_DONE;\n"
    "mov.u32 n, 0;\n"
    "W_LOOP:\n"
    "mbarrier.try_wait.parity.shared::cta.b64 p, [%0], %1;\n"
    "@p bra W_DONE;\n"
    "add.u32 n, n, 1;\n"
    "setp.lt.u32 p, n, 0x1000000;\n"
    "@p bra W_LOOP;\n"
    "trap;\n"
    "W_DONE:\n}" :: "r"(bar), "r"(par) : "memory");
}
__device__ __forceinline__ void tma_load(uint32_t dst, const CUtensorMap* m, uint32_t bar, int c0, int c1) {
  asm volatile("cp.async.bulk.tensor.2d.shared::cluster.global.mbarrier::complete_tx::bytes [%0], [%1, {%3, %4}], [%2];" :: "r"(dst), "l"(m), "r"(bar), "r"(c0), "r"(c1) : "memory");
}
__device__ __forceinline__ void tma_load_mc(uint32_t dst, const CUtensorMap* m, uint32_t bar, int c0, int c1) {
  asm volatile("cp.async.bulk.tensor.2d.shared::cluster.global.mbarrier::complete_tx::bytes.multicast::cluster [%0], [%1, {%3, %4}], [%2], %5;" :: "r"(dst), "l"(m), "r"(bar), "r"(c0), "r"(c1), "h"((uint16_t)3) : "memory");
}
__device__ __forceinline__ void tma_load3_mc(uint32_t dst, const CUtensorMap* m, uint32_t bar, int c0, int c2) {
  asm volatile("cp.async.bulk.tensor.3d.shared::cluster.global.mbarrier::complete_tx::bytes.multicast::cluster [%0], [%1, {%3, %4, 0}], [%2], %5;" :: "r"(dst), "l"(m), "r"(bar), "r"(c0), "r"(c2), "h"((uint16_t)3) : "memory");
}
__device__ __forceinline__ void tma_prefetch(const CUtensorMap* m, int c0, int c1) {
  asm volatile("cp.async.bulk.prefetch.tensor.2d.L2.global [%0, {%1, %2}];" :: "l"(m), "r"(c0), "r"(c1) : "memory");
}
__device__ __forceinline__ void bulk_prefetch(const void* p, uint32_t bytes) {
  asm volatile("cp.async.bulk.prefetch.L2.global [%0], %1;" :: "l"(p), "r"(bytes) : "memory");
}
__device__ __forceinline__ void bulk_load(uint32_t dst, const void* src, uint32_t bytes, uint32_t bar) {
  asm volatile("cp.async.bulk.shared::cluster.global.mbarrier::complete_tx::bytes [%0], [%1], %2, [%3];" :: "r"(dst), "l"(src), "r"(bytes), "r"(bar) : "memory");
}
__device__ __forceinline__ void fence_async_smem() { asm volatile("fence.proxy.async.shared::cta;" ::: "memory"); }
__device__ __forceinline__ void bar_sync(int id, int n) { asm volatile("bar.sync %0, %1;" :: "r"(id), "r"(n) : "memory"); }
__device__ __forceinline__ void bar_arrive(int id, int n) { asm volatile("bar.arrive %0, %1;" :: "r"(id), "r"(n) : "memory"); }
__device__ __forceinline__ void wg_fence() { asm volatile("wgmma.fence.sync.aligned;" ::: "memory"); }
__device__ __forceinline__ void wg_commit() { asm volatile("wgmma.commit_group.sync.aligned;" ::: "memory"); }
template <int N> __device__ __forceinline__ void wg_wait() { asm volatile("wgmma.wait_group.sync.aligned %0;" :: "n"(N) : "memory"); }
template <int N> __device__ __forceinline__ void pin(float (&r)[N]) {
#pragma unroll
  for (int i = 0; i < N; i++) asm volatile("" : "+f"(r[i]) :: "memory");
}
template <int N> __device__ __forceinline__ void pin(uint32_t (&r)[N]) {
#pragma unroll
  for (int i = 0; i < N; i++) asm volatile("" : "+r"(r[i]) :: "memory");
}
__device__ __forceinline__ uint32_t make_desc(uint32_t addr, uint32_t lbo) { return (addr >> 4) | ((lbo >> 4) << 16); }
__device__ __forceinline__ float ex2(float x) { float y; asm("ex2.approx.ftz.f32 %0, %1;" : "=f"(y) : "f"(x)); return y; }
__device__ __forceinline__ float tanh_fast(float x) { float y; asm("tanh.approx.f32 %0, %1;" : "=f"(y) : "f"(x)); return y; }
__device__ __forceinline__ uint32_t pack2(float lo, float hi) { uint32_t r; asm("cvt.rn.bf16x2.f32 %0, %1, %2;" : "=r"(r) : "f"(hi), "f"(lo)); return r; }
__device__ __forceinline__ float blo(uint32_t w) { return __uint_as_float(w << 16); }
__device__ __forceinline__ float bhi(uint32_t w) { return __uint_as_float(w & 0xffff0000u); }
__device__ __forceinline__ float bround(float x) { return blo(pack2(x, 0.f)); }
__device__ __forceinline__ uint32_t hfma2(uint32_t a, uint32_t b, uint32_t c) { uint32_t r; asm("fma.rn.bf16x2 %0, %1, %2, %3;" : "=r"(r) : "r"(a), "r"(b), "r"(c)); return r; }
__device__ __forceinline__ uint32_t one_plus(uint32_t w) { return pack2(1.f + blo(w), 1.f + bhi(w)); }
__device__ __forceinline__ void ldsm4(uint32_t addr, uint32_t& a, uint32_t& b, uint32_t& c, uint32_t& d) {
  asm volatile("ldmatrix.sync.aligned.m8n8.x4.shared.b16 {%0,%1,%2,%3}, [%4];" : "=r"(a), "=r"(b), "=r"(c), "=r"(d) : "r"(addr) : "memory");
}
__device__ __forceinline__ void stsm4(uint32_t addr, uint32_t a, uint32_t b, uint32_t c, uint32_t d) {
  asm volatile("stmatrix.sync.aligned.m8n8.x4.shared.b16 [%0], {%1,%2,%3,%4};" :: "r"(addr), "r"(a), "r"(b), "r"(c), "r"(d) : "memory");
}
__device__ __forceinline__ void sts128(uint32_t addr, uint32_t a, uint32_t b, uint32_t c, uint32_t d) {
  asm volatile("st.shared.v4.b32 [%0], {%1,%2,%3,%4};" :: "r"(addr), "r"(a), "r"(b), "r"(c), "r"(d) : "memory");
}
__device__ __forceinline__ uint4 lds128(uint32_t addr) {
  uint4 v; asm volatile("ld.shared.v4.b32 {%0,%1,%2,%3}, [%4];" : "=r"(v.x), "=r"(v.y), "=r"(v.z), "=r"(v.w) : "r"(addr) : "memory"); return v;
}
__device__ __forceinline__ void sts32(uint32_t addr, uint32_t v) { asm volatile("st.shared.b32 [%0], %1;" :: "r"(addr), "r"(v) : "memory"); }
__device__ __forceinline__ uint32_t lds32(uint32_t addr) { uint32_t v; asm volatile("ld.shared.b32 %0, [%1];" : "=r"(v) : "r"(addr) : "memory"); return v; }
__device__ __forceinline__ uint4 ldg_nc128(const void* p) {
  uint4 v; asm volatile("ld.global.nc.v4.b32 {%0,%1,%2,%3}, [%4];" : "=r"(v.x), "=r"(v.y), "=r"(v.z), "=r"(v.w) : "l"(p)); return v;
}
__device__ __forceinline__ uint32_t ldg_nc32(const void* p) { uint32_t v; asm volatile("ld.global.nc.b32 %0, [%1];" : "=r"(v) : "l"(p)); return v; }
__device__ __forceinline__ void stg128(void* p, uint32_t a, uint32_t b, uint32_t c, uint32_t d) {
  asm volatile("st.global.v4.b32 [%0], {%1,%2,%3,%4};" :: "l"(p), "r"(a), "r"(b), "r"(c), "r"(d) : "memory");
}
template <int OFF> __device__ __forceinline__ void stg128o(void* p, uint32_t a, uint32_t b, uint32_t c, uint32_t d) {
  asm volatile("st.global.v4.b32 [%0 + %5], {%1,%2,%3,%4};" :: "l"(p), "r"(a), "r"(b), "r"(c), "r"(d), "n"(OFF) : "memory");
}
template <int C> __device__ __forceinline__ void store_chunks(void* p, const float (&acc)[128]) {
  stg128o<C * 512>(p, pack2(acc[8 * C], acc[8 * C + 1]), pack2(acc[8 * C + 2], acc[8 * C + 3]), pack2(acc[8 * C + 4], acc[8 * C + 5]), pack2(acc[8 * C + 6], acc[8 * C + 7]));
  if constexpr (C < 15) store_chunks<C + 1>(p, acc);
}
__device__ __forceinline__ unsigned long long ld_ll(const unsigned long long* p) {
  unsigned long long v; asm volatile("ld.relaxed.gpu.global.b64 %0, [%1];" : "=l"(v) : "l"(p) : "memory"); return v;
}
__device__ __forceinline__ void st_ll(unsigned long long* p, uint32_t val, uint32_t tag) {
  asm volatile("st.relaxed.gpu.global.b64 [%0], %1;" :: "l"(p), "l"(((unsigned long long)tag << 32) | val) : "memory");
}
__device__ __forceinline__ void flag_set(unsigned int* f, uint32_t tag) { asm volatile("st.release.gpu.global.u32 [%0], %1;" :: "l"(f), "r"(tag) : "memory"); }
__device__ __forceinline__ uint32_t flag_get(const unsigned int* f) { uint32_t v; asm volatile("ld.acquire.gpu.global.u32 %0, [%1];" : "=r"(v) : "l"(f) : "memory"); return v; }
__device__ __forceinline__ void trap_if(bool c) { asm volatile("{\n.reg .pred p;\nsetp.ne.u32 p, %0, 0;\n@p trap;\n}" :: "r"((uint32_t)c)); }
__device__ __forceinline__ float rcp_fast(float x) { float y; asm("rcp.approx.ftz.f32 %0, %1;" : "=f"(y) : "f"(x)); return y; }
__device__ __forceinline__ float sqrt_fast(float x) { float y; asm("sqrt.approx.ftz.f32 %0, %1;" : "=f"(y) : "f"(x)); return y; }
__device__ __forceinline__ float silu_bf(float x) { return bround(x * rcp_fast(1.f + ex2(-1.4426950408889634f * x))); }
__device__ __forceinline__ float ln_rstd(float mean, float ex2mean) { return rcp_fast(bround(sqrt_fast(bround(bround(fmaxf(ex2mean - mean * mean, 0.f)) + 1e-5f)))); }
__device__ __forceinline__ uint4 ldg_cg128(const void* p) {
  uint4 v; asm volatile("ld.global.cg.v4.b32 {%0,%1,%2,%3}, [%4];" : "=r"(v.x), "=r"(v.y), "=r"(v.z), "=r"(v.w) : "l"(p) : "memory"); return v;
}
__device__ __forceinline__ float xreduce8(float (&a)[8], int lane) {
#pragma unroll
  for (int i = 0; i < 4; i++) { const bool up = lane & 16; const float snd = up ? a[i] : a[i + 4], kp = up ? a[i + 4] : a[i]; a[i] = kp + __shfl_xor_sync(~0u, snd, 16); }
#pragma unroll
  for (int i = 0; i < 2; i++) { const bool up = lane & 8; const float snd = up ? a[i] : a[i + 2], kp = up ? a[i + 2] : a[i]; a[i] = kp + __shfl_xor_sync(~0u, snd, 8); }
  const bool up = lane & 4; const float snd = up ? a[0] : a[1], kp = up ? a[1] : a[0];
  const float r = kp + __shfl_xor_sync(~0u, snd, 4);
  return r + __shfl_xor_sync(~0u, r, 2);
}
__device__ __forceinline__ void mma16816(float& c0, float& c1, float& c2, float& c3, uint32_t a0, uint32_t a1, uint32_t a2, uint32_t a3, uint32_t b0, uint32_t b1) {
  asm("mma.sync.aligned.m16n8k16.row.col.f32.bf16.bf16.f32 {%0,%1,%2,%3}, {%4,%5,%6,%7}, {%8,%9}, {%0,%1,%2,%3};"
      : "+f"(c0), "+f"(c1), "+f"(c2), "+f"(c3) : "r"(a0), "r"(a1), "r"(a2), "r"(a3), "r"(b0), "r"(b1));
}

template <int N> struct IC { __device__ constexpr operator int() const { return N; } };

__device__ __forceinline__ void wgmma_rs_n128_t0(float (&d)[64], uint32_t a0, uint32_t a1, uint32_t a2, uint32_t a3, uint32_t db, int scale_d) {
  asm volatile(
    "{\n.reg .pred p;\n.reg .b64 db;\nmov.b64 db, {%68, %70};\nsetp.ne.b32 p, %69, 0;\n"
    "wgmma.mma_async.sync.aligned.m64n128k16.f32.bf16.bf16 {"
    "%0, %1, %2, %3, %4, %5, %6, %7, %8, %9, %10, %11, %12, %13, %14, %15, "
    "%16, %17, %18, %19, %20, %21, %22, %23, %24, %25, %26, %27, %28, %29, %30, %31, "
    "%32, %33, %34, %35, %36, %37, %38, %39, %40, %41, %42, %43, %44, %45, %46, %47, "
    "%48, %49, %50, %51, %52, %53, %54, %55, %56, %57, %58, %59, %60, %61, %62, %63"
    "}, {%64, %65, %66, %67}, db, p, 1, 1, 0;\n}\n"
    : "+f"(d[0]), "+f"(d[1]), "+f"(d[2]), "+f"(d[3]), "+f"(d[4]), "+f"(d[5]), "+f"(d[6]), "+f"(d[7]),
      "+f"(d[8]), "+f"(d[9]), "+f"(d[10]), "+f"(d[11]), "+f"(d[12]), "+f"(d[13]), "+f"(d[14]), "+f"(d[15]),
      "+f"(d[16]), "+f"(d[17]), "+f"(d[18]), "+f"(d[19]), "+f"(d[20]), "+f"(d[21]), "+f"(d[22]), "+f"(d[23]),
      "+f"(d[24]), "+f"(d[25]), "+f"(d[26]), "+f"(d[27]), "+f"(d[28]), "+f"(d[29]), "+f"(d[30]), "+f"(d[31]),
      "+f"(d[32]), "+f"(d[33]), "+f"(d[34]), "+f"(d[35]), "+f"(d[36]), "+f"(d[37]), "+f"(d[38]), "+f"(d[39]),
      "+f"(d[40]), "+f"(d[41]), "+f"(d[42]), "+f"(d[43]), "+f"(d[44]), "+f"(d[45]), "+f"(d[46]), "+f"(d[47]),
      "+f"(d[48]), "+f"(d[49]), "+f"(d[50]), "+f"(d[51]), "+f"(d[52]), "+f"(d[53]), "+f"(d[54]), "+f"(d[55]),
      "+f"(d[56]), "+f"(d[57]), "+f"(d[58]), "+f"(d[59]), "+f"(d[60]), "+f"(d[61]), "+f"(d[62]), "+f"(d[63])
    : "r"(a0), "r"(a1), "r"(a2), "r"(a3), "r"(db), "r"(scale_d), "r"(0x40000040u));
}
__device__ __forceinline__ void wgmma_rs_n128_t1(float (&d)[64], uint32_t a0, uint32_t a1, uint32_t a2, uint32_t a3, uint32_t db, int scale_d) {
  asm volatile(
    "{\n.reg .pred p;\n.reg .b64 db;\nmov.b64 db, {%68, %70};\nsetp.ne.b32 p, %69, 0;\n"
    "wgmma.mma_async.sync.aligned.m64n128k16.f32.bf16.bf16 {"
    "%0, %1, %2, %3, %4, %5, %6, %7, %8, %9, %10, %11, %12, %13, %14, %15, "
    "%16, %17, %18, %19, %20, %21, %22, %23, %24, %25, %26, %27, %28, %29, %30, %31, "
    "%32, %33, %34, %35, %36, %37, %38, %39, %40, %41, %42, %43, %44, %45, %46, %47, "
    "%48, %49, %50, %51, %52, %53, %54, %55, %56, %57, %58, %59, %60, %61, %62, %63"
    "}, {%64, %65, %66, %67}, db, p, 1, 1, 1;\n}\n"
    : "+f"(d[0]), "+f"(d[1]), "+f"(d[2]), "+f"(d[3]), "+f"(d[4]), "+f"(d[5]), "+f"(d[6]), "+f"(d[7]),
      "+f"(d[8]), "+f"(d[9]), "+f"(d[10]), "+f"(d[11]), "+f"(d[12]), "+f"(d[13]), "+f"(d[14]), "+f"(d[15]),
      "+f"(d[16]), "+f"(d[17]), "+f"(d[18]), "+f"(d[19]), "+f"(d[20]), "+f"(d[21]), "+f"(d[22]), "+f"(d[23]),
      "+f"(d[24]), "+f"(d[25]), "+f"(d[26]), "+f"(d[27]), "+f"(d[28]), "+f"(d[29]), "+f"(d[30]), "+f"(d[31]),
      "+f"(d[32]), "+f"(d[33]), "+f"(d[34]), "+f"(d[35]), "+f"(d[36]), "+f"(d[37]), "+f"(d[38]), "+f"(d[39]),
      "+f"(d[40]), "+f"(d[41]), "+f"(d[42]), "+f"(d[43]), "+f"(d[44]), "+f"(d[45]), "+f"(d[46]), "+f"(d[47]),
      "+f"(d[48]), "+f"(d[49]), "+f"(d[50]), "+f"(d[51]), "+f"(d[52]), "+f"(d[53]), "+f"(d[54]), "+f"(d[55]),
      "+f"(d[56]), "+f"(d[57]), "+f"(d[58]), "+f"(d[59]), "+f"(d[60]), "+f"(d[61]), "+f"(d[62]), "+f"(d[63])
    : "r"(a0), "r"(a1), "r"(a2), "r"(a3), "r"(db), "r"(scale_d), "r"(0x40000040u));
}
__device__ __forceinline__ void wgmma_ss_n256_t1(float (&d)[128], uint32_t da, uint32_t db, int scale_d, uint32_t db_hi = 0x40000040u) {
  asm volatile(
    "{\n.reg .pred p;\n.reg .b64 da, db;\nmov.b64 da, {%128, %131};\nmov.b64 db, {%129, %132};\nsetp.ne.b32 p, %130, 0;\n"
    "wgmma.mma_async.sync.aligned.m64n256k16.f32.bf16.bf16 {"
    "%0, %1, %2, %3, %4, %5, %6, %7, %8, %9, %10, %11, %12, %13, %14, %15, "
    "%16, %17, %18, %19, %20, %21, %22, %23, %24, %25, %26, %27, %28, %29, %30, %31, "
    "%32, %33, %34, %35, %36, %37, %38, %39, %40, %41, %42, %43, %44, %45, %46, %47, "
    "%48, %49, %50, %51, %52, %53, %54, %55, %56, %57, %58, %59, %60, %61, %62, %63, "
    "%64, %65, %66, %67, %68, %69, %70, %71, %72, %73, %74, %75, %76, %77, %78, %79, "
    "%80, %81, %82, %83, %84, %85, %86, %87, %88, %89, %90, %91, %92, %93, %94, %95, "
    "%96, %97, %98, %99, %100, %101, %102, %103, %104, %105, %106, %107, %108, %109, %110, %111, "
    "%112, %113, %114, %115, %116, %117, %118, %119, %120, %121, %122, %123, %124, %125, %126, %127"
    "}, da, db, p, 1, 1, 0, 1;\n}\n"
    : "+f"(d[0]), "+f"(d[1]), "+f"(d[2]), "+f"(d[3]), "+f"(d[4]), "+f"(d[5]), "+f"(d[6]), "+f"(d[7]),
      "+f"(d[8]), "+f"(d[9]), "+f"(d[10]), "+f"(d[11]), "+f"(d[12]), "+f"(d[13]), "+f"(d[14]), "+f"(d[15]),
      "+f"(d[16]), "+f"(d[17]), "+f"(d[18]), "+f"(d[19]), "+f"(d[20]), "+f"(d[21]), "+f"(d[22]), "+f"(d[23]),
      "+f"(d[24]), "+f"(d[25]), "+f"(d[26]), "+f"(d[27]), "+f"(d[28]), "+f"(d[29]), "+f"(d[30]), "+f"(d[31]),
      "+f"(d[32]), "+f"(d[33]), "+f"(d[34]), "+f"(d[35]), "+f"(d[36]), "+f"(d[37]), "+f"(d[38]), "+f"(d[39]),
      "+f"(d[40]), "+f"(d[41]), "+f"(d[42]), "+f"(d[43]), "+f"(d[44]), "+f"(d[45]), "+f"(d[46]), "+f"(d[47]),
      "+f"(d[48]), "+f"(d[49]), "+f"(d[50]), "+f"(d[51]), "+f"(d[52]), "+f"(d[53]), "+f"(d[54]), "+f"(d[55]),
      "+f"(d[56]), "+f"(d[57]), "+f"(d[58]), "+f"(d[59]), "+f"(d[60]), "+f"(d[61]), "+f"(d[62]), "+f"(d[63]),
      "+f"(d[64]), "+f"(d[65]), "+f"(d[66]), "+f"(d[67]), "+f"(d[68]), "+f"(d[69]), "+f"(d[70]), "+f"(d[71]),
      "+f"(d[72]), "+f"(d[73]), "+f"(d[74]), "+f"(d[75]), "+f"(d[76]), "+f"(d[77]), "+f"(d[78]), "+f"(d[79]),
      "+f"(d[80]), "+f"(d[81]), "+f"(d[82]), "+f"(d[83]), "+f"(d[84]), "+f"(d[85]), "+f"(d[86]), "+f"(d[87]),
      "+f"(d[88]), "+f"(d[89]), "+f"(d[90]), "+f"(d[91]), "+f"(d[92]), "+f"(d[93]), "+f"(d[94]), "+f"(d[95]),
      "+f"(d[96]), "+f"(d[97]), "+f"(d[98]), "+f"(d[99]), "+f"(d[100]), "+f"(d[101]), "+f"(d[102]), "+f"(d[103]),
      "+f"(d[104]), "+f"(d[105]), "+f"(d[106]), "+f"(d[107]), "+f"(d[108]), "+f"(d[109]), "+f"(d[110]), "+f"(d[111]),
      "+f"(d[112]), "+f"(d[113]), "+f"(d[114]), "+f"(d[115]), "+f"(d[116]), "+f"(d[117]), "+f"(d[118]), "+f"(d[119]),
      "+f"(d[120]), "+f"(d[121]), "+f"(d[122]), "+f"(d[123]), "+f"(d[124]), "+f"(d[125]), "+f"(d[126]), "+f"(d[127])
    : "r"(da), "r"(db), "r"(scale_d), "r"(0x40000040u), "r"(db_hi));
}
__device__ __forceinline__ void wgmma_rs_n256_t1(float (&d)[128], uint32_t a0, uint32_t a1, uint32_t a2, uint32_t a3, uint32_t db, int scale_d) {
  asm volatile(
    "{\n.reg .pred p;\n.reg .b64 db;\nmov.b64 db, {%132, %134};\nsetp.ne.b32 p, %133, 0;\n"
    "wgmma.mma_async.sync.aligned.m64n256k16.f32.bf16.bf16 {"
    "%0, %1, %2, %3, %4, %5, %6, %7, %8, %9, %10, %11, %12, %13, %14, %15, "
    "%16, %17, %18, %19, %20, %21, %22, %23, %24, %25, %26, %27, %28, %29, %30, %31, "
    "%32, %33, %34, %35, %36, %37, %38, %39, %40, %41, %42, %43, %44, %45, %46, %47, "
    "%48, %49, %50, %51, %52, %53, %54, %55, %56, %57, %58, %59, %60, %61, %62, %63, "
    "%64, %65, %66, %67, %68, %69, %70, %71, %72, %73, %74, %75, %76, %77, %78, %79, "
    "%80, %81, %82, %83, %84, %85, %86, %87, %88, %89, %90, %91, %92, %93, %94, %95, "
    "%96, %97, %98, %99, %100, %101, %102, %103, %104, %105, %106, %107, %108, %109, %110, %111, "
    "%112, %113, %114, %115, %116, %117, %118, %119, %120, %121, %122, %123, %124, %125, %126, %127"
    "}, {%128, %129, %130, %131}, db, p, 1, 1, 1;\n}\n"
    : "+f"(d[0]), "+f"(d[1]), "+f"(d[2]), "+f"(d[3]), "+f"(d[4]), "+f"(d[5]), "+f"(d[6]), "+f"(d[7]),
      "+f"(d[8]), "+f"(d[9]), "+f"(d[10]), "+f"(d[11]), "+f"(d[12]), "+f"(d[13]), "+f"(d[14]), "+f"(d[15]),
      "+f"(d[16]), "+f"(d[17]), "+f"(d[18]), "+f"(d[19]), "+f"(d[20]), "+f"(d[21]), "+f"(d[22]), "+f"(d[23]),
      "+f"(d[24]), "+f"(d[25]), "+f"(d[26]), "+f"(d[27]), "+f"(d[28]), "+f"(d[29]), "+f"(d[30]), "+f"(d[31]),
      "+f"(d[32]), "+f"(d[33]), "+f"(d[34]), "+f"(d[35]), "+f"(d[36]), "+f"(d[37]), "+f"(d[38]), "+f"(d[39]),
      "+f"(d[40]), "+f"(d[41]), "+f"(d[42]), "+f"(d[43]), "+f"(d[44]), "+f"(d[45]), "+f"(d[46]), "+f"(d[47]),
      "+f"(d[48]), "+f"(d[49]), "+f"(d[50]), "+f"(d[51]), "+f"(d[52]), "+f"(d[53]), "+f"(d[54]), "+f"(d[55]),
      "+f"(d[56]), "+f"(d[57]), "+f"(d[58]), "+f"(d[59]), "+f"(d[60]), "+f"(d[61]), "+f"(d[62]), "+f"(d[63]),
      "+f"(d[64]), "+f"(d[65]), "+f"(d[66]), "+f"(d[67]), "+f"(d[68]), "+f"(d[69]), "+f"(d[70]), "+f"(d[71]),
      "+f"(d[72]), "+f"(d[73]), "+f"(d[74]), "+f"(d[75]), "+f"(d[76]), "+f"(d[77]), "+f"(d[78]), "+f"(d[79]),
      "+f"(d[80]), "+f"(d[81]), "+f"(d[82]), "+f"(d[83]), "+f"(d[84]), "+f"(d[85]), "+f"(d[86]), "+f"(d[87]),
      "+f"(d[88]), "+f"(d[89]), "+f"(d[90]), "+f"(d[91]), "+f"(d[92]), "+f"(d[93]), "+f"(d[94]), "+f"(d[95]),
      "+f"(d[96]), "+f"(d[97]), "+f"(d[98]), "+f"(d[99]), "+f"(d[100]), "+f"(d[101]), "+f"(d[102]), "+f"(d[103]),
      "+f"(d[104]), "+f"(d[105]), "+f"(d[106]), "+f"(d[107]), "+f"(d[108]), "+f"(d[109]), "+f"(d[110]), "+f"(d[111]),
      "+f"(d[112]), "+f"(d[113]), "+f"(d[114]), "+f"(d[115]), "+f"(d[116]), "+f"(d[117]), "+f"(d[118]), "+f"(d[119]),
      "+f"(d[120]), "+f"(d[121]), "+f"(d[122]), "+f"(d[123]), "+f"(d[124]), "+f"(d[125]), "+f"(d[126]), "+f"(d[127])
    : "r"(a0), "r"(a1), "r"(a2), "r"(a3), "r"(db), "r"(scale_d), "r"(0x40000040u));
}
__device__ __forceinline__ void wgmma_ss_n192_t1(float (&d)[96], uint32_t da, uint32_t db, int scale_d, uint32_t db_hi = 0x40000040u) {
  asm volatile(
    "{\n.reg .pred p;\n.reg .b64 da, db;\nmov.b64 da, {%96, %99};\nmov.b64 db, {%97, %100};\nsetp.ne.b32 p, %98, 0;\n"
    "wgmma.mma_async.sync.aligned.m64n192k16.f32.bf16.bf16 {"
    "%0, %1, %2, %3, %4, %5, %6, %7, %8, %9, %10, %11, %12, %13, %14, %15, "
    "%16, %17, %18, %19, %20, %21, %22, %23, %24, %25, %26, %27, %28, %29, %30, %31, "
    "%32, %33, %34, %35, %36, %37, %38, %39, %40, %41, %42, %43, %44, %45, %46, %47, "
    "%48, %49, %50, %51, %52, %53, %54, %55, %56, %57, %58, %59, %60, %61, %62, %63, "
    "%64, %65, %66, %67, %68, %69, %70, %71, %72, %73, %74, %75, %76, %77, %78, %79, "
    "%80, %81, %82, %83, %84, %85, %86, %87, %88, %89, %90, %91, %92, %93, %94, %95"
    "}, da, db, p, 1, 1, 0, 1;\n}\n"
    : "+f"(d[0]), "+f"(d[1]), "+f"(d[2]), "+f"(d[3]), "+f"(d[4]), "+f"(d[5]), "+f"(d[6]), "+f"(d[7]),
      "+f"(d[8]), "+f"(d[9]), "+f"(d[10]), "+f"(d[11]), "+f"(d[12]), "+f"(d[13]), "+f"(d[14]), "+f"(d[15]),
      "+f"(d[16]), "+f"(d[17]), "+f"(d[18]), "+f"(d[19]), "+f"(d[20]), "+f"(d[21]), "+f"(d[22]), "+f"(d[23]),
      "+f"(d[24]), "+f"(d[25]), "+f"(d[26]), "+f"(d[27]), "+f"(d[28]), "+f"(d[29]), "+f"(d[30]), "+f"(d[31]),
      "+f"(d[32]), "+f"(d[33]), "+f"(d[34]), "+f"(d[35]), "+f"(d[36]), "+f"(d[37]), "+f"(d[38]), "+f"(d[39]),
      "+f"(d[40]), "+f"(d[41]), "+f"(d[42]), "+f"(d[43]), "+f"(d[44]), "+f"(d[45]), "+f"(d[46]), "+f"(d[47]),
      "+f"(d[48]), "+f"(d[49]), "+f"(d[50]), "+f"(d[51]), "+f"(d[52]), "+f"(d[53]), "+f"(d[54]), "+f"(d[55]),
      "+f"(d[56]), "+f"(d[57]), "+f"(d[58]), "+f"(d[59]), "+f"(d[60]), "+f"(d[61]), "+f"(d[62]), "+f"(d[63]),
      "+f"(d[64]), "+f"(d[65]), "+f"(d[66]), "+f"(d[67]), "+f"(d[68]), "+f"(d[69]), "+f"(d[70]), "+f"(d[71]),
      "+f"(d[72]), "+f"(d[73]), "+f"(d[74]), "+f"(d[75]), "+f"(d[76]), "+f"(d[77]), "+f"(d[78]), "+f"(d[79]),
      "+f"(d[80]), "+f"(d[81]), "+f"(d[82]), "+f"(d[83]), "+f"(d[84]), "+f"(d[85]), "+f"(d[86]), "+f"(d[87]),
      "+f"(d[88]), "+f"(d[89]), "+f"(d[90]), "+f"(d[91]), "+f"(d[92]), "+f"(d[93]), "+f"(d[94]), "+f"(d[95])
    : "r"(da), "r"(db), "r"(scale_d), "r"(0x40000040u), "r"(db_hi));
}

#define TS(k)
#define TSD(k)
#define TG(k)

constexpr int B_PP = 1;
constexpr int B_CONS = 3;
constexpr int B_WG = 4;
constexpr int B_AUX = 6;
constexpr int B_X = 7;

template <bool SWP>
__global__ void __cluster_dims__(2, 1, 1) __launch_bounds__(384, 1)
fused_kernel(const __grid_constant__ Maps mp, const __nv_bfloat16* __restrict__ x, const __nv_bfloat16* __restrict__ kc,
             const __nv_bfloat16* __restrict__ wo, const __nv_bfloat16* __restrict__ wg, const __nv_bfloat16* __restrict__ wu,
             const __nv_bfloat16* __restrict__ wd, const __nv_bfloat16* __restrict__ cvec, const __nv_bfloat16* __restrict__ wmod,
             __nv_bfloat16* __restrict__ out) {
  extern __shared__ __align__(1024) uint8_t sm_raw[];
  const uint32_t sb = smem_u32(sm_raw);
  const int tid = threadIdx.x, lane = tid & 31;
  const int warp = __shfl_sync(~0u, tid >> 5, 0);
  const int b = blockIdx.x;
  const uint32_t rank = b & 1;
  const int g = (b >> 1) & 7;
  const int rt = (b >> 4) * 2 + rank;
  auto FULL = [&](int h) { return sb + OFF_BAR + 8 * h; };
  auto EMPTY = [&](int h) { return sb + OFF_BAR + 112 + 8 * h; };
  auto AFULL = [&](int s) { return sb + OFF_BAR + 200 + 8 * s; };
  auto AEMPTY = [&](int s) { return sb + OFF_BAR + 232 + 8 * s; };
  auto XFULL = [&](int r) { return sb + OFF_BAR + 288 + 8 * r; };

  if (warp < 4) {
    asm volatile("setmaxnreg.dec.sync.aligned.u32 %0;" :: "n"(PROD_REGS));
    if (tid == 0) {
      trap_if(sb & 1023);
#pragma unroll
      for (int i = 39; i >= 0; i--) mbar_init(sb + OFF_BAR + 8 * i, (i >= 14 && i < 28) || (i >= 32 && i < 36) ? 16 : 1);
      asm volatile("fence.mbarrier_init.release.cluster;" ::: "memory");
      fence_async_smem();
    }
    __syncwarp();
    asm volatile("barrier.cluster.arrive.relaxed.aligned;" ::: "memory");
    if (warp == 0) {
      if (lane < 4) mbar_expect_tx(XFULL(lane), SLOT);
      __syncwarp();
      tma_load(sb + (lane & 7) * HALF + (lane >> 3) * 4096, &mp.x, XFULL(lane >> 3), (lane & 7) * 64, rt * 128 + (lane >> 3) * 32);
    }
    asm volatile("barrier.cluster.wait.aligned;" ::: "memory");
    if (warp >= 2) {
      const int j = tid - 64;
      mbar_wait(AFULL(3), 0);
      float a[8];
#pragma unroll
      for (int i = 0; i < 8; i++) a[i] = 0.f;
#pragma unroll 1
      for (int k = j >> 1; k < 512; k += 32) {
        const uint4 w = ldg_nc128(wmod + (size_t)k * 3072 + 1024 + b * 16 + (j & 1) * 8);
        const float sc = silu_bf(__bfloat162float(cvec[k]));
        a[0] += sc * blo(w.x); a[1] += sc * bhi(w.x); a[2] += sc * blo(w.y); a[3] += sc * bhi(w.y);
        a[4] += sc * blo(w.z); a[5] += sc * bhi(w.z); a[6] += sc * blo(w.w); a[7] += sc * bhi(w.w);
      }
      const float r = xreduce8(a, lane);
      if ((lane & 2) == 0) sts32(sb + OFF_RED2 + ((j >> 5) * 16 + (lane & 1) * 8 + (lane >> 2)) * 4, __float_as_uint(r));
      bar_sync(B_AUX, 64);
      if (j < 8) {
        const float v0 = __uint_as_float(lds32(sb + OFF_RED2 + 8 * j)) + __uint_as_float(lds32(sb + OFF_RED2 + 64 + 8 * j));
        const float v1 = __uint_as_float(lds32(sb + OFF_RED2 + 8 * j + 4)) + __uint_as_float(lds32(sb + OFF_RED2 + 68 + 8 * j));
        uint32_t w = pack2(v0, v1);
        if ((b >> 5) == 2) w = one_plus(w);
        g_sync.late[(b >> 2) * 32 + (j & 3) * 8 + (b & 3) * 2 + (j >> 2)] = w;
        __syncwarp(0xffu);
        if (j == 0) asm volatile("red.release.gpu.global.add.u32 [%0], 1;" :: "l"(&g_sync.late_cnt) : "memory");
      }
    } else if (tid == 0) {
      uint32_t pe = 0x3f00;
      int h6 = 8, gi = 0, dj = 0;
#pragma unroll 1
      for (int i = 0; i < 110; i++) {
        if (i == 32) {
#pragma unroll 1
          for (int u = 0; u < 129; u++) {
            if (u == 127) continue;
            const int isv = u != 0 && (u & 1) == 0, t = isv ? (u >> 1) - 1 : (u + 1) >> 1;
            const int s = isv ? 4 - (t & 1) : 5 + (t & 1);
            if (t < 2) { mbar_wait(EMPTY(2 * s), (pe >> (2 * s)) & 1); mbar_wait(EMPTY(2 * s + 1), (pe >> (2 * s)) & 1); pe ^= 3u << (2 * s); }
            else mbar_wait(AEMPTY(s), ((t >> 1) & 1) ^ 1);
            mbar_expect_tx(AFULL(s), SLOT);
            tma_load_mc(sb + s * SLOT + rank * HALF, isv ? &mp.v : &mp.k, AFULL(s), rank * 64, g * SEQ + (t & 15) * 128);
          }
          h6 = 10;
        }
        const CUtensorMap* m; int h, xx, yy;
        const bool gu = i >= 64 && gi < 32 && gi < 24 + 2 * dj;
        if (i < 32) { m = &mp.wq; h = h6; xx = g * 512 + (i < 16 ? 256 : 0) + rank * 128; yy = (i & 15) * 32; }
        else if (i < 64) { m = &mp.wo; h = (0x7698dcba >> ((i & 7) * 4)) & 15; xx = ((i >> 4) & 1) * 256 + rank * 128; yy = g * 512 + (i & 15) * 32; }
        else if (gu) { m = &mp.gu; h = h6; xx = g * FS + (gi >> 4) * 128 + rank * 64; yy = (gi & 15) * 32; gi++; }
        else { m = &mp.wd; h = dj < 7 ? dj : dj < 13 ? h6 : 7; xx = (h >= 7 ? 256 : 0) + rank * 128; yy = g * FS + (h >= 7 ? h - 7 : h) * 32; dj++; }
        if (h == h6 && (i < 32 || i >= 64)) h6 = h6 == 13 ? 8 : h6 + 1;
        if ((i >> 3) == 4) mbar_wait(AEMPTY(h >> 1), 1);
        else { mbar_wait(EMPTY(h), (pe >> h) & 1); pe ^= 1u << h; }
        const uint32_t dst = sb + h * HALF + rank * 8192;
        if (gu) {
          mbar_expect_tx(FULL(h), gi > 16 ? 12288 : HALF);
          tma_load3_mc(dst, m, FULL(h), xx, yy);
          if (gi <= 16 || rank == 0) tma_load3_mc(dst + 4096, m, FULL(h), xx + 32, yy);
        } else {
          mbar_expect_tx(FULL(h), HALF);
          tma_load_mc(dst, m, FULL(h), xx, yy);
          tma_load_mc(dst + 4096, m, FULL(h), xx + 64, yy);
        }
      }
    } else if (warp == 1) {
      if (lane < 8) tma_prefetch(&mp.wq, g * 512 + (rt < 8 ? 256 : 0) + (lane & 3) * 64, (rt & 7) * 64 + (lane >> 2) * 32);
      mbar_wait(EMPTY(8), 0);
      if (lane < 4) tma_prefetch((lane & 2) ? &mp.v : &mp.k, (lane & 1) * 64, g * SEQ + rt * 128);
      mbar_wait(AFULL(3), 0);
      if (lane < 4) bulk_prefetch((const uint8_t*)(lane == 0 ? wo : lane == 1 ? wg : lane == 2 ? wu : wd) + (size_t)b * (lane ? 14336 : 32768), lane ? 14336 : 32768);
      const uint32_t tag = lds32(sb + OFF_EPOCH);
      int n = 0;
      while ((int)(flag_get(&g_sync.late_cnt) - tag * 128) < 0) { __nanosleep(200); trap_if(++n > (1 << 22)); }
#pragma unroll 1
      for (int phase = 0; phase < 3; phase++) {
        bar_sync(B_X, 288);
        if (lane < 8) mbar_expect_tx(FULL(lane), HALF);
        __syncwarp();
        bool done = lane >= 8;
        n = 0;
        while (!__all_sync(~0u, done)) {
          if (!done && flag_get(&g_sync.flag[(phase * 16 + rt) * 32 + lane]) == tag) {
            asm volatile("fence.proxy.async.global;" ::: "memory");
            if (phase == 1) {
#pragma unroll 1
              for (int k = 0; k < 8; k++) tma_load(sb + k * HALF + lane * 2048, &mp.h2, FULL(k), k * 64, rt * 128 + lane * 16);
            } else {
              bulk_load(sb + lane * HALF, g_part + ((size_t)(rt * 8 + g) * 8 + lane) * 1024, HALF, FULL(lane));
            }
            done = true;
          }
          trap_if(++n > (1 << 24));
        }
      }
    }
  } else {
    asm volatile("barrier.cluster.arrive.relaxed.aligned;" ::: "memory");
    asm volatile("setmaxnreg.inc.sync.aligned.u32 %0;" :: "n"(CONS_REGS));
    const int ct = tid - 128, wid = warp - 4, cw = wid >> 2;
    uint32_t rel0;
    asm volatile("mapa.shared::cluster.u32 %0, %1, %2;" : "=r"(rel0) : "r"(EMPTY(0)), "r"(lane & 1));
    auto release = [&](int h) { if (lane < 2) asm volatile("mbarrier.arrive.shared::cluster.b64 _, [%0];" :: "r"(rel0 + 8 * h) : "memory"); };
    auto release_a = [&](int s) { release(15 + s); };
    uint32_t pf = 0;
    auto wait_full = [&](int h) { mbar_wait(FULL(h), (pf >> h) & 1); pf ^= 1u << h; };
    const uint32_t frag_row = wid * 16 + (lane & 15);
    const uint32_t fa0 = sb + frag_row * 128 + (((lane >> 4) ^ (lane & 7)) << 4);
    auto frag_addr = [&](int slot, int kk) { return (fa0 ^ ((kk & 3) << 5)) + slot * SLOT + (kk >> 2) * HALF; };
    uint32_t tag;
    uint32_t nm, rh, rl;
    TS(31);

    {
      asm volatile("ld.relaxed.gpu.global.u32 %0, [%1];" : "=r"(tag) : "l"(&g_sync.epoch) : "memory");
      const uint4 w0 = ldg_nc128(wmod + (size_t)ct * 3072 + b * 8), w1 = ldg_nc128(wmod + (size_t)(ct + 256) * 3072 + b * 8);
      const float c0 = __bfloat162float(cvec[ct]), c1 = __bfloat162float(cvec[ct + 256]);
      asm volatile("barrier.cluster.wait.aligned;" ::: "memory");
      tag += 1;
      if (ct == 0) sts32(sb + OFF_EPOCH, tag);
      {
        const float s0 = silu_bf(c0), s1 = silu_bf(c1);
        float a[8] = {s0 * blo(w0.x) + s1 * blo(w1.x), s0 * bhi(w0.x) + s1 * bhi(w1.x), s0 * blo(w0.y) + s1 * blo(w1.y), s0 * bhi(w0.y) + s1 * bhi(w1.y),
                      s0 * blo(w0.z) + s1 * blo(w1.z), s0 * bhi(w0.z) + s1 * bhi(w1.z), s0 * blo(w0.w) + s1 * blo(w1.w), s0 * bhi(w0.w) + s1 * bhi(w1.w)};
        float r = xreduce8(a, lane);
        r += __shfl_xor_sync(~0u, r, 1);
        if ((lane & 3) == 0) sts32(sb + OFF_RED + ((lane >> 2) * 8 + wid) * 4, __float_as_uint(r));
        bar_sync(B_CONS, 256);
        if (ct < 8) {
          const uint4 u = lds128(sb + OFF_RED + ct * 32), w = lds128(sb + OFF_RED + ct * 32 + 16);
          const float v0 = ((__uint_as_float(u.x) + __uint_as_float(u.y)) + (__uint_as_float(u.z) + __uint_as_float(u.w))) + ((__uint_as_float(w.x) + __uint_as_float(w.y)) + (__uint_as_float(w.z) + __uint_as_float(w.w)));
          const float v1 = __shfl_xor_sync(0xffu, v0, 1);
          if ((ct & 1) == 0) st_ll(&g_sync.modll[b * 4 + (ct >> 1)], pack2(v0, v1), tag);
        }
      }
      TS(0);
      mbar_wait(XFULL(wid >> 1), 0);
      TS(19);
      {
        float su[8], d0[8], d1[8];
#pragma unroll
        for (int i = 0; i < 8; i++) { su[i] = 0.f; d0[i] = 0.f; d1[i] = 0.f; }
#pragma unroll 1
        for (int sl = 0; sl < 8; sl++) {
          uint32_t a[16];
#pragma unroll
          for (int kk = 0; kk < 4; kk++) ldsm4(frag_addr(0, kk) + sl * HALF, a[4 * kk], a[4 * kk + 1], a[4 * kk + 2], a[4 * kk + 3]);
#pragma unroll
          for (int kk = 0; kk < 4; kk++) {
            const int o = (kk & 1) * 4;
            mma16816(su[o], su[o + 1], su[o + 2], su[o + 3], a[4 * kk], a[4 * kk + 1], a[4 * kk + 2], a[4 * kk + 3], 0x3f803f80u, 0x3f803f80u);
            mma16816(d0[o], d0[o + 1], d0[o + 2], d0[o + 3], a[4 * kk], a[4 * kk + 1], a[4 * kk + 2], a[4 * kk + 3], a[4 * kk], a[4 * kk + 2]);
            mma16816(d1[o], d1[o + 1], d1[o + 2], d1[o + 3], a[4 * kk], a[4 * kk + 1], a[4 * kk + 2], a[4 * kk + 3], a[4 * kk + 1], a[4 * kk + 3]);
          }
        }
        su[0] += su[4]; su[2] += su[6]; d0[0] += d0[4]; d0[1] += d0[5]; d1[2] += d1[6]; d1[3] += d1[7];
        const bool odd = lane & 4;
        const int src = (lane & 7) * 4 + ((lane & 7) >> 1);
        const float qa = __shfl_sync(~0u, odd ? d0[1] : d0[0], src), qb = __shfl_sync(~0u, odd ? d1[3] : d1[2], src);
        const float sa = __shfl_sync(~0u, su[0], src), sc = __shfl_sync(~0u, su[2], src);
        const float mean = ((lane & 8) ? sc : sa) * (1.f / DM);
        const float r = ln_rstd(mean, ((lane & 8) ? qb : qa) * (1.f / DM));
        const float m = -bround(mean) * r;
        nm = pack2(m, m); rh = pack2(r, r);
        const float lo = r - blo(rh);
        rl = pack2(lo, lo);
      }
      TS(1);
      {
        const int c = ct & 127;
        unsigned long long pk[4];
        int n = 0;
        while (true) {
#pragma unroll
          for (int i = 0; i < 4; i++) pk[i] = ld_ll(&g_sync.modll[i * 128 + c]);
          if ((((uint32_t)(pk[0] >> 32) ^ tag) | ((uint32_t)(pk[1] >> 32) ^ tag) | ((uint32_t)(pk[2] >> 32) ^ tag) | ((uint32_t)(pk[3] >> 32) ^ tag)) == 0) break;
          trap_if(++n > (1 << 24));
        }
#pragma unroll
        for (int i = 0; i < 4; i++) sts32(sb + OFF_MODSM + (i * 128 + c) * 4, i < 2 ? (uint32_t)pk[i] : one_plus((uint32_t)pk[i]));
      }
      bar_sync(B_WG + cw, 128);
      TS(2);
    }
    TS(3);

    const uint32_t dA0 = make_desc(sb + cw * 8192, 16);
    const uint32_t dB0 = make_desc(sb, 4096);
    uint32_t q[32];

    {
      auto norm = [&](int k) {
        const uint32_t ad = (fa0 ^ ((lane >> 4) * 48) ^ ((k & 1) << 6)) + (k >> 1) * HALF;
        const uint32_t md = sb + OFF_MODSM + k * 64 + (lane >> 4) * 32;
        uint4 u = lds128(ad), w = lds128(ad ^ 16);
        const uint4 s0 = lds128(md), s1 = lds128(md + 16), g0 = lds128(md + 1024), g1 = lds128(md + 1040);
        auto nrm = [&](uint32_t xv, uint32_t gw, uint32_t sw) { return hfma2(hfma2(xv, rh, hfma2(xv, rl, nm)), gw, sw); };
        u.x = nrm(u.x, g0.x, s0.x); u.y = nrm(u.y, g0.y, s0.y); u.z = nrm(u.z, g0.z, s0.z); u.w = nrm(u.w, g0.w, s0.w);
        w.x = nrm(w.x, g1.x, s1.x); w.y = nrm(w.y, g1.y, s1.y); w.z = nrm(w.z, g1.z, s1.z); w.w = nrm(w.w, g1.w, s1.w);
        sts128(ad, u.x, u.y, u.z, u.w);
        sts128(ad ^ 16, w.x, w.y, w.z, w.w);
        fence_async_smem();
        bar_sync(B_WG + cw, 128);
      };
      uint32_t held[64];
      float acc[128];
      int h6 = 8, prev = 8;
#pragma unroll 1
      for (int pass = 0; pass < 2; pass++) {
#pragma unroll 1
        for (int k = pass ? 0 : -NORM_AHEAD; k < 16; k++) {
          if (k >= 0) {
            wait_full(h6);
            wg_fence();
#pragma unroll
            for (int ks = 0; ks < 2; ks++) wgmma_ss_n256_t1(acc, dA0 + (k >> 1) * 1024 + (k & 1) * 4 + ks * 2, dB0 + h6 * 1024 + ks * 128, (k | ks) != 0);
            wg_commit();
          }
          if (pass == 0 && k + NORM_AHEAD < 16) norm(k + NORM_AHEAD);
          if (k > 0) { wg_wait<1>(); release(prev); }
          if (k >= 0) { prev = h6; h6 = h6 == 13 ? 8 : h6 + 1; }
          if (k == 0) TS(26);
        }
        wg_wait<0>(); pin(acc);
        release(prev);
        if (pass == 0) {
#pragma unroll
          for (int j = 0; j < 64; j++) held[j] = pack2(acc[2 * j], acc[2 * j + 1]);
          pin(held);
        }
      }
      release(6); release(7);
#pragma unroll
      for (int j = 0; j < 32; j++) q[j] = pack2(acc[2 * j], acc[2 * j + 1]);
#pragma unroll
      for (int kk = 0; kk < 8; kk++) {
        stsm4(frag_addr(0, kk), pack2(acc[64 + 8 * kk], acc[65 + 8 * kk]), pack2(acc[66 + 8 * kk], acc[67 + 8 * kk]), pack2(acc[68 + 8 * kk], acc[69 + 8 * kk]), pack2(acc[70 + 8 * kk], acc[71 + 8 * kk]));
        stsm4(frag_addr(1, kk), held[4 * kk], held[4 * kk + 1], held[4 * kk + 2], held[4 * kk + 3]);
        stsm4(frag_addr(2, kk), held[32 + 4 * kk], held[33 + 4 * kk], held[34 + 4 * kk], held[35 + 4 * kk]);
      }
      pin(q);
    }
    TS(4);

    {
      const float cl2 = 0.08838834764831845f * 1.4426950408889634f;
      const uint32_t dK0 = make_desc(sb + 5 * SLOT, 16);
      const uint32_t dV0 = make_desc(sb + 3 * SLOT, 16384);
      float o[64], s[64];
      uint32_t p[32];
      float ms0 = 0.f, ms1 = 0.f, l0 = 1.f, l1 = 1.f, t0, t1;
      auto qk = [&](int st) {
#pragma unroll
        for (int kk = 0; kk < 8; kk++) wgmma_rs_n128_t0(s, q[4 * kk], q[4 * kk + 1], q[4 * kk + 2], q[4 * kk + 3], dK0 + st * 2048 + (kk >> 2) * 1024 + (kk & 3) * 2, kk != 0);
        wg_commit();
      };
      auto pv = [&](int st, int acc) {
#pragma unroll
        for (int kk = 0; kk < 8; kk++) wgmma_rs_n128_t1(o, p[4 * kk], p[4 * kk + 1], p[4 * kk + 2], p[4 * kk + 3], dV0 + st * 2048 + kk * 128, (kk != 0) | acc);
        wg_commit();
      };
      auto rowmax = [&](float& a, float& c) {
        float u[4], w[4];
#pragma unroll
        for (int j = 0; j < 4; j++) { u[j] = fmaxf(s[4 * j], s[4 * j + 1]); w[j] = fmaxf(s[4 * j + 2], s[4 * j + 3]); }
#pragma unroll
        for (int j = 4; j < 16; j++) { u[j & 3] = fmaxf(fmaxf(u[j & 3], s[4 * j]), s[4 * j + 1]); w[j & 3] = fmaxf(fmaxf(w[j & 3], s[4 * j + 2]), s[4 * j + 3]); }
        float x0 = fmaxf(fmaxf(u[0], u[1]), fmaxf(u[2], u[3])), x1 = fmaxf(fmaxf(w[0], w[1]), fmaxf(w[2], w[3]));
        x0 = fmaxf(x0, __shfl_xor_sync(~0u, x0, 1)); x1 = fmaxf(x1, __shfl_xor_sync(~0u, x1, 1));
        x0 = fmaxf(x0, __shfl_xor_sync(~0u, x0, 2)); x1 = fmaxf(x1, __shfl_xor_sync(~0u, x1, 2));
        a = x0 * cl2; c = x1 * cl2;
      };
      auto exprange = [&](auto j0, auto j1) {
#pragma unroll
        for (int j = j0; j < j1; j++) {
          s[4 * j] = ex2(fmaf(s[4 * j], cl2, -ms0)); s[4 * j + 1] = ex2(fmaf(s[4 * j + 1], cl2, -ms0));
          s[4 * j + 2] = ex2(fmaf(s[4 * j + 2], cl2, -ms1)); s[4 * j + 3] = ex2(fmaf(s[4 * j + 3], cl2, -ms1));
          if (j == 0) { t0 = s[0] + s[1]; t1 = s[2] + s[3]; } else { t0 += s[4 * j] + s[4 * j + 1]; t1 += s[4 * j + 2] + s[4 * j + 3]; }
        }
      };
      auto cvtp = [&]() {
#pragma unroll
        for (int j = 0; j < 32; j++) p[j] = pack2(s[2 * j], s[2 * j + 1]);
      };
      auto inv_l = [&](float& i0, float& i1) {
        float a = l0 + __shfl_xor_sync(~0u, l0, 1), c = l1 + __shfl_xor_sync(~0u, l1, 1);
        a += __shfl_xor_sync(~0u, a, 2); c += __shfl_xor_sync(~0u, c, 2);
        i0 = rcp_fast(a); i1 = rcp_fast(c);
      };
      if (cw == 0) bar_arrive(B_PP, 256);
      mbar_wait(AFULL(5), 0);
      float i0, i1;
#pragma unroll 1
      for (int t = 0; t < 64; t++) {
        const int st = t & 1;
        bar_sync(B_PP + cw, 256);
        wg_fence();
        qk(st);
        if (t > 0) mbar_wait(AFULL(3 + st), ((t - 1) >> 1) & 1);
        wg_fence();
        pv(st, (t & 15) != 1);
        bar_arrive(B_PP + (cw ^ 1), 256);
        const bool first = (t & 15) == 0;
        if (first) inv_l(i0, i1);
        wg_wait<1>(); pin(s);
        release_a(5 + st);
        if (first) { rowmax(ms0, ms1); l0 = 0.f; l1 = 0.f; }
        exprange(IC<0>(), IC<EXP_SPLIT>());
        pin(s);
        mbar_wait_hot(AFULL(6 - st), ((t + 1 - (t == 63 ? 2 : 0)) >> 1) & 1);
        wg_wait<0>(); pin(o); pin(p);
        if (t > 0) release_a(3 + st);
        exprange(IC<EXP_SPLIT>(), IC<16>());
        if (first && t > 0) {
          const int slot = (t >> 4) - 1;
#pragma unroll
          for (int j = 0; j < 16; j++) { p[2 * j] = pack2(o[4 * j] * i0, o[4 * j + 1] * i0); p[2 * j + 1] = pack2(o[4 * j + 2] * i1, o[4 * j + 3] * i1); }
#pragma unroll
          for (int kk = 0; kk < 8; kk++) stsm4(frag_addr(slot, kk), p[4 * kk], p[4 * kk + 1], p[4 * kk + 2], p[4 * kk + 3]);
          fence_async_smem();
        }
        cvtp();
        if (__any_sync(~0u, !(t0 + t1 <= 1.2089258e24f))) {
          float4 sr[16];
          uint2 pr[16];
          const uint32_t* kp = (const uint32_t*)(kc + (size_t)(g * SEQ + (t & 15) * 128 + (lane >> 2)) * DH) + (lane & 3);
          float x0 = ms0, x1 = ms1;
#pragma unroll 1
          for (int j = 0; j < 16; j++) {
            float4 c = {0.f, 0.f, 0.f, 0.f};
#pragma unroll
            for (int kk = 0; kk < 8; kk++)
              mma16816(c.x, c.y, c.z, c.w, q[4 * kk], q[4 * kk + 1], q[4 * kk + 2], q[4 * kk + 3], ldg_nc32(kp + j * 512 + kk * 8), ldg_nc32(kp + j * 512 + kk * 8 + 4));
            sr[j] = c;
            x0 = fmaxf(x0, fmaxf(c.x, c.y) * cl2); x1 = fmaxf(x1, fmaxf(c.z, c.w) * cl2);
          }
          x0 = fmaxf(x0, __shfl_xor_sync(~0u, x0, 1)); x1 = fmaxf(x1, __shfl_xor_sync(~0u, x1, 1));
          x0 = fmaxf(x0, __shfl_xor_sync(~0u, x0, 2)); x1 = fmaxf(x1, __shfl_xor_sync(~0u, x1, 2));
          const float a0 = ex2(ms0 - x0), a1 = ex2(ms1 - x1);
          ms0 = x0; ms1 = x1; l0 *= a0; l1 *= a1; t0 = 0.f; t1 = 0.f;
#pragma unroll 1
          for (int j = 0; j < 16; j++) {
            const float4 c = sr[j];
            const float e0 = ex2(fmaf(c.x, cl2, -x0)), e1 = ex2(fmaf(c.y, cl2, -x0)), e2 = ex2(fmaf(c.z, cl2, -x1)), e3 = ex2(fmaf(c.w, cl2, -x1));
            t0 += e0 + e1; t1 += e2 + e3;
            pr[j] = make_uint2(pack2(e0, e1), pack2(e2, e3));
          }
#pragma unroll
          for (int j = 0; j < 16; j++) { o[4 * j] *= a0; o[4 * j + 1] *= a0; o[4 * j + 2] *= a1; o[4 * j + 3] *= a1; p[2 * j] = pr[j].x; p[2 * j + 1] = pr[j].y; }
        }
        l0 += t0; l1 += t1;
        if ((t & 15) == 15 && t < 63) {
#pragma unroll
          for (int kk = 0; kk < 8; kk++) ldsm4(frag_addr(t >> 4, kk), q[4 * kk], q[4 * kk + 1], q[4 * kk + 2], q[4 * kk + 3]);
        }
        pin(p); pin(o); pin(q);
        asm volatile("" : "+f"(l0), "+f"(l1) :: "memory");
      }
      mbar_wait(AFULL(3), 1);
      if (cw == 0) bar_sync(B_PP, 256);
      wg_fence();
      pv(0, 1);
      inv_l(i0, i1);
      wg_wait<0>(); pin(o);
      release_a(3);
#pragma unroll
      for (int j = 0; j < 16; j++) { q[2 * j] = pack2(o[4 * j] * i0, o[4 * j + 1] * i0); q[2 * j + 1] = pack2(o[4 * j + 2] * i1, o[4 * j + 3] * i1); }
      pin(q);
    }
    TS(10);

    uint4* const part_w = g_part + ((size_t)(rt * 8 + wid) * 8 + g) * 1024 + lane;
    auto store_part = [&](const float (&acc)[128], int pass) { store_chunks<0>(part_w + pass * 512, acc); };
    auto publish = [&](int phase) {
      bar_sync(B_CONS, 256);
      if (ct == 0) flag_set(&g_sync.flag[(phase * 16 + rt) * 32 + g], tag);
    };
    auto gather = [&](float (&y)[32]) {
#pragma unroll
      for (int i = 0; i < 32; i++) y[i] = 0.f;
#pragma unroll 1
      for (int sg = 0; sg < 8; sg++) {
        wait_full(sg);
#pragma unroll
        for (int c = 0; c < 4; c++) {
          const uint4 w = lds128(sb + sg * HALF + wid * 2048 + c * 512 + lane * 16);
          y[8 * c] += blo(w.x); y[8 * c + 1] += bhi(w.x); y[8 * c + 2] += blo(w.y); y[8 * c + 3] += bhi(w.y);
          y[8 * c + 4] += blo(w.z); y[8 * c + 5] += bhi(w.z); y[8 * c + 6] += blo(w.w); y[8 * c + 7] += bhi(w.w);
        }
      }
    };
    auto late_vec = [&](uint32_t (&r)[8], int which) {
      const uint4 u = ldg_cg128(&g_sync.late[which * 256 + wid * 32 + (lane & 3) * 8]), w = ldg_cg128(&g_sync.late[which * 256 + wid * 32 + (lane & 3) * 8 + 4]);
      r[0] = u.x; r[1] = u.y; r[2] = u.z; r[3] = u.w; r[4] = w.x; r[5] = w.y; r[6] = w.z; r[7] = w.w;
    };
    auto write_rows = [&](const uint32_t (&w)[16], __nv_bfloat16* dst) {
      const uint32_t st = sb + wid * 2048;
      __syncwarp();
#pragma unroll
      for (int c = 0; c < 4; c++) stsm4(st + (lane & 15) * 128 + (((c * 2 + (lane >> 4)) ^ (lane & 7)) << 4), w[4 * c], w[4 * c + 1], w[4 * c + 2], w[4 * c + 3]);
      __syncwarp();
#pragma unroll
      for (int i = 0; i < 4; i++) {
        const int r = i * 4 + (lane >> 3);
        const uint4 u = lds128(st + r * 128 + (((lane & 7) ^ (r & 7)) << 4));
        stg128(dst + (size_t)(rt * 128 + g * 16 + r) * DM + wid * 64 + (lane & 7) * 8, u.x, u.y, u.z, u.w);
      }
    };
    const int mcol = wid * 32 + (lane & 3);

    {
      float acc[128];
#pragma unroll 1
      for (int pass = 0; pass < 2; pass++) {
        int prev = 0;
#pragma unroll 1
        for (int k = 0; k < 12; k++) {
          const int h = (0x7698dcba >> ((k & 7) * 4)) & 15;
          wait_full(h);
          wg_fence();
#pragma unroll
          for (int ks = 0; ks < 2; ks++) wgmma_ss_n256_t1(acc, dA0 + (k >> 1) * 1024 + (k & 1) * 4 + ks * 2, dB0 + h * 1024 + ks * 128, (k | ks) != 0);
          wg_commit();
          if (k > 0) { wg_wait<1>(); release(prev); }
          prev = h;
        }
#pragma unroll
        for (int k = 0; k < 4; k++) {
          const int h = k < 2 ? 8 + k : 4 + k;
          wait_full(h);
          wg_fence();
#pragma unroll
          for (int ks = 0; ks < 2; ks++) wgmma_rs_n256_t1(acc, q[8 * k + 4 * ks], q[8 * k + 4 * ks + 1], q[8 * k + 4 * ks + 2], q[8 * k + 4 * ks + 3], dB0 + h * 1024 + ks * 128, 1);
          wg_commit();
          wg_wait<1>();
          if (k < 3 || pass == 0) release(k == 0 ? 13 : k == 1 ? 8 : k == 2 ? 9 : 6);
        }
        wg_wait<0>(); pin(acc); pin(q);
        if (pass == 0) release(7); else bar_arrive(B_X, 288);
        TSD(22 + pass);
        store_part(acc, pass);
      }
    }
    TS(24);
    publish(0);
    TS(11);

    uint32_t x1[16];
    {
      uint32_t ga[8], cb[8], sbv[8];
      const uint32_t* xp = (const uint32_t*)(x + (size_t)(rt * 128 + g * 16 + (lane >> 2)) * DM) + mcol;
#pragma unroll
      for (int j = 0; j < 8; j++) { x1[2 * j] = ldg_nc32(xp + 4 * j); x1[2 * j + 1] = ldg_nc32(xp + 8 * (DM / 2) + 4 * j); }
      mbar_wait(FULL(0), pf & 1);
      late_vec(ga, 0); late_vec(sbv, 1); late_vec(cb, 2);
      float y[32];
      gather(y);
      TS(12);
      float s0 = 0.f, q0 = 0.f, s1 = 0.f, q1 = 0.f;
#pragma unroll
      for (int j = 0; j < 8; j++) {
        y[4 * j] = fmaf(blo(ga[j]), y[4 * j], blo(x1[2 * j])); y[4 * j + 1] = fmaf(bhi(ga[j]), y[4 * j + 1], bhi(x1[2 * j]));
        y[4 * j + 2] = fmaf(blo(ga[j]), y[4 * j + 2], blo(x1[2 * j + 1])); y[4 * j + 3] = fmaf(bhi(ga[j]), y[4 * j + 3], bhi(x1[2 * j + 1]));
        x1[2 * j] = pack2(y[4 * j], y[4 * j + 1]); x1[2 * j + 1] = pack2(y[4 * j + 2], y[4 * j + 3]);
        s0 += y[4 * j] + y[4 * j + 1]; q0 = fmaf(y[4 * j], y[4 * j], q0); q0 = fmaf(y[4 * j + 1], y[4 * j + 1], q0);
        s1 += y[4 * j + 2] + y[4 * j + 3]; q1 = fmaf(y[4 * j + 2], y[4 * j + 2], q1); q1 = fmaf(y[4 * j + 3], y[4 * j + 3], q1);
      }
#pragma unroll
      for (int o = 1; o < 4; o <<= 1) { s0 += __shfl_xor_sync(~0u, s0, o); q0 += __shfl_xor_sync(~0u, q0, o); s1 += __shfl_xor_sync(~0u, s1, o); q1 += __shfl_xor_sync(~0u, q1, o); }
      if ((lane & 3) == 0) sts128(sb + OFF_MODSM + (wid * 8 + (lane >> 2)) * 16, __float_as_uint(s0), __float_as_uint(q0), __float_as_uint(s1), __float_as_uint(q1));
      bar_sync(B_CONS, 256);
      s0 = q0 = s1 = q1 = 0.f;
#pragma unroll 2
      for (int w = 0; w < 8; w++) { const uint4 u = lds128(sb + OFF_MODSM + (w * 8 + (lane >> 2)) * 16); s0 += __uint_as_float(u.x); q0 += __uint_as_float(u.y); s1 += __uint_as_float(u.z); q1 += __uint_as_float(u.w); }
      const float m0 = s0 * (1.f / DM), m1 = s1 * (1.f / DM);
      const float r0 = ln_rstd(m0, q0 * (1.f / DM)), r1 = ln_rstd(m1, q1 * (1.f / DM));
      const float n0 = -bround(m0) * r0, n1 = -bround(m1) * r1;
      uint32_t hw[16];
#pragma unroll
      for (int j = 0; j < 8; j++) {
        hw[2 * j] = hfma2(pack2(fmaf(y[4 * j], r0, n0), fmaf(y[4 * j + 1], r0, n0)), cb[j], sbv[j]);
        hw[2 * j + 1] = hfma2(pack2(fmaf(y[4 * j + 2], r1, n1), fmaf(y[4 * j + 3], r1, n1)), cb[j], sbv[j]);
      }
      write_rows(hw, g_h2);
      bar_arrive(B_X, 288);
      publish(1);
      pin(x1);
    }
    TS(13);

    {
      uint32_t act[56];
      int h6 = 10, prev = 10;
      const uint32_t dG0 = make_desc(sb, 2048);
      auto swiglu = [&](float a0, float a1, float b0, float b1) {
        const float h0 = 0.5f * (SWP ? b0 : a0), h1 = 0.5f * (SWP ? b1 : a1);
        const float m0 = h0 * (SWP ? a0 : b0), m1 = h1 * (SWP ? a1 : b1);
        return pack2(fmaf(m0, tanh_fast(h0), m0), fmaf(m1, tanh_fast(h1), m1));
      };
      {
        float acc[128];
#pragma unroll 1
        for (int k = 0; k < 16; k++) {
          if ((k & 1) == 0) wait_full(k >> 1);
          wait_full(h6);
          wg_fence();
#pragma unroll
          for (int ks = 0; ks < 2; ks++) wgmma_ss_n256_t1(acc, dA0 + (k >> 1) * 1024 + (k & 1) * 4 + ks * 2, dG0 + h6 * 1024 + ks * 64, (k | ks) != 0, 0x80000020u);
          wg_commit();
          if (k > 0) { wg_wait<1>(); release(prev); }
          prev = h6; h6 = h6 == 13 ? 8 : h6 + 1;
          if (k == 0) TS(14);
        }
        wg_wait<0>(); pin(acc);
        release(prev);
        TS(20);
#pragma unroll
        for (int j = 0; j < 32; j++) { const int a = (j >> 3) * 32 + (j & 7) * 2; act[j] = swiglu(acc[a], acc[a + 1], acc[a + 16], acc[a + 17]); }
      }
      {
        float acc[96];
#pragma unroll 1
        for (int k = 0; k < 16; k++) {
          wait_full(h6);
          wg_fence();
#pragma unroll
          for (int ks = 0; ks < 2; ks++) wgmma_ss_n192_t1(acc, dA0 + (k >> 1) * 1024 + (k & 1) * 4 + ks * 2, dG0 + h6 * 1024 + ks * 64, (k | ks) != 0, 0x80000020u);
          wg_commit();
          if (k > 0) { wg_wait<1>(); release(prev); if ((k & 1) == 0) release((k >> 1) - 1); }
          prev = h6; h6 = h6 == 13 ? 8 : h6 + 1;
        }
        wg_wait<0>(); pin(acc);
        release(prev); release(7);
        TS(21);
#pragma unroll
        for (int j = 0; j < 24; j++) { const int a = (j >> 3) * 32 + (j & 7) * 2; act[32 + j] = swiglu(acc[a], acc[a + 1], acc[a + 16], acc[a + 17]); }
      }
      pin(act);
      TS(15);
      float acc[128];
#pragma unroll 1
      for (int pass = 0; pass < 2; pass++) {
#pragma unroll 1
        for (int k = 0; k < 7; k++) wait_full(pass * 7 + k);
        wg_fence();
#pragma unroll
        for (int ks = 0; ks < 14; ks++) wgmma_rs_n256_t1(acc, act[4 * ks], act[4 * ks + 1], act[4 * ks + 2], act[4 * ks + 3], dB0 + pass * 7168 + (ks >> 1) * 1024 + (ks & 1) * 128, ks != 0);
        wg_commit();
        wg_wait<0>(); pin(acc); pin(act);
        if (pass == 1) bar_arrive(B_X, 288);
        TS(25);
        store_part(acc, pass);
      }
    }
    publish(2);
    asm volatile("barrier.cluster.arrive.relaxed.aligned;" ::: "memory");
    TS(16);

    {
      uint32_t gb[8];
      late_vec(gb, 3);
      float y[32];
      gather(y);
      TS(17);
      if (b == 0 && ct == 0) g_sync.epoch = tag;
      uint32_t ow[16];
#pragma unroll
      for (int j = 0; j < 8; j++) {
        ow[2 * j] = pack2(fmaf(blo(gb[j]), y[4 * j], blo(x1[2 * j])), fmaf(bhi(gb[j]), y[4 * j + 1], bhi(x1[2 * j])));
        ow[2 * j + 1] = pack2(fmaf(blo(gb[j]), y[4 * j + 2], blo(x1[2 * j + 1])), fmaf(bhi(gb[j]), y[4 * j + 3], bhi(x1[2 * j + 1])));
      }
      write_rows(ow, out);
    }
    TS(18); TG(126);
    asm volatile("barrier.cluster.wait.aligned;" ::: "memory");
  }
}

typedef CUresult (*EncodeFn)(CUtensorMap*, CUtensorMapDataType, cuuint32_t, void*, const cuuint64_t*, const cuuint64_t*, const cuuint32_t*, const cuuint32_t*,
                             CUtensorMapInterleave, CUtensorMapSwizzle, CUtensorMapL2promotion, CUtensorMapFloatOOBfill);

void make_map(EncodeFn fn, CUtensorMap* m, const void* p, uint64_t rows, uint64_t cols, uint32_t box_rows) {
  cuuint64_t dims[2] = {cols, rows};
  cuuint64_t strides[1] = {cols * 2};
  cuuint32_t box[2] = {64, box_rows};
  cuuint32_t es[2] = {1, 1};
  fn(m, CU_TENSOR_MAP_DATA_TYPE_BFLOAT16, 2, const_cast<void*>(p), dims, strides, box, es, CU_TENSOR_MAP_INTERLEAVE_NONE, CU_TENSOR_MAP_SWIZZLE_128B,
     CU_TENSOR_MAP_L2_PROMOTION_L2_128B, CU_TENSOR_MAP_FLOAT_OOB_FILL_NONE);
}

}

extern "C" void kernel_launch(void* const* d_in, const int* in_sizes, int n_in, void* d_out, int out_size) {
  (void)in_sizes; (void)n_in; (void)out_size;
  typedef const __nv_bfloat16* P;
  P x = (P)d_in[0], k = (P)d_in[1], v = (P)d_in[2], wq = (P)d_in[3], wo = (P)d_in[4];
  P wg = (P)d_in[6], wu = (P)d_in[7], wd = (P)d_in[8], c = (P)d_in[9], wmod = (P)d_in[10];
  static EncodeFn fn = nullptr;
  static void* h2p = nullptr;
  if (!fn) {
    void* p = nullptr;
    cudaDriverEntryPointQueryResult qr;
    cudaGetDriverEntryPoint("cuTensorMapEncodeTiled", &p, cudaEnableDefault, &qr);
    fn = (EncodeFn)p;
    cudaGetSymbolAddress(&h2p, g_h2);
    cudaFuncSetAttribute(fused_kernel<false>, cudaFuncAttributeMaxDynamicSharedMemorySize, SMEM_BYTES);
    cudaFuncSetAttribute(fused_kernel<true>, cudaFuncAttributeMaxDynamicSharedMemorySize, SMEM_BYTES);
  }
  Maps mp;
  make_map(fn, &mp.wq, wq, 512, 4096, 32);
  make_map(fn, &mp.k, k, 8 * SEQ, DH, 128);
  make_map(fn, &mp.v, v, 8 * SEQ, DH, 128);
  make_map(fn, &mp.wo, wo, 4096, DM, 32);
  {
    P lo = wg < wu ? wg : wu, hi = wg < wu ? wu : wg;
    cuuint64_t dims[3] = {FF, DM, 2};
    cuuint64_t strides[2] = {FF * 2, (cuuint64_t)((const char*)hi - (const char*)lo)};
    cuuint32_t box[3] = {32, 32, 2};
    cuuint32_t es[3] = {1, 1, 1};
    fn(&mp.gu, CU_TENSOR_MAP_DATA_TYPE_BFLOAT16, 3, (void*)lo, dims, strides, box, es, CU_TENSOR_MAP_INTERLEAVE_NONE, CU_TENSOR_MAP_SWIZZLE_64B,
       CU_TENSOR_MAP_L2_PROMOTION_L2_128B, CU_TENSOR_MAP_FLOAT_OOB_FILL_NONE);
  }
  make_map(fn, &mp.wd, wd, FF, DM, 32);
  make_map(fn, &mp.h2, h2p, SEQ, DM, 16);
  make_map(fn, &mp.x, x, SEQ, DM, 32);
  if (wu < wg) fused_kernel<true><<<128, 384, SMEM_BYTES>>>(mp, x, k, wo, wg, wu, wd, c, wmod, (__nv_bfloat16*)d_out);
  else fused_kernel<false><<<128, 384, SMEM_BYTES>>>(mp, x, k, wo, wg, wu, wd, c, wmod, (__nv_bfloat16*)d_out);
}
```

```cpp
#include <cuda_runtime.h>
#include <cuda_bf16.h>
#include <cuda.h>
#include <stdint.h>

namespace {

constexpr int SEQ = 2048, DM = 512, DH = 128, FF = 1792, FS = 224;
constexpr int SLOT = 32768, HALF = 16384;
constexpr int OFF_BAR = 7 * SLOT;
constexpr int OFF_MODSM = OFF_BAR + 336;
constexpr int OFF_RED = OFF_MODSM + 2048;
constexpr int SMEM_BYTES = 232448;
static_assert(OFF_RED + 256 <= SMEM_BYTES, "smem");

constexpr int CONS_REGS = 232, PROD_REGS = 40;
constexpr int EXP_SPLIT = 11;
constexpr int LAG = 2;
constexpr float BIAS = 100.f, REDO_SUM = 1073741824.f;

struct __align__(128) Sync {
  unsigned long long modll[4 * 512];
  unsigned int late[1024];
  unsigned int flag[5 * 16 * 32];
  unsigned int late_cnt;
  unsigned int pad[31];
  unsigned int epoch;
};
struct Scratch {
  Sync sync;
  uint4 part[16 * 65536];
  uint4 act[16 * 8 * 14 * 256];
  uint4 x1[16 * 8 * 4 * 8 * 32];
  uint4 h2[16 * 8 * 1024];
};
__device__ Scratch g_scratch;

struct Maps { CUtensorMap wq, k, v, wo, gu, wd, x; };

__device__ __forceinline__ uint32_t smem_u32(const void* p) { return (uint32_t)__cvta_generic_to_shared(p); }
__device__ __forceinline__ void mbar_init(uint32_t bar, uint32_t cnt) { asm volatile("mbarrier.init.shared::cta.b64 [%0], %1;" :: "r"(bar), "r"(cnt) : "memory"); }
__device__ __forceinline__ void mbar_expect_tx(uint32_t bar, uint32_t bytes) { asm volatile("mbarrier.arrive.expect_tx.shared::cta.b64 _, [%0], %1;" :: "r"(bar), "r"(bytes) : "memory"); }
__device__ __forceinline__ void mbar_wait(uint32_t bar, uint32_t par) {
  asm volatile(
    "{\n.reg .pred p;\n.reg .u32 n;\n"
    "mov.u32 n, 0;\n"
    "W_LOOP:\n"
    "mbarrier.try_wait.parity.shared::cta.b64 p, [%0], %1;\n"
    "@p bra W_DONE;\n"
    "add.u32 n, n, 1;\n"
    "setp.lt.u32 p, n, 0x400000;\n"
    "@p bra W_LOOP;\n"
    "trap;\n"
    "W_DONE:\n}" :: "r"(bar), "r"(par) : "memory");
}
__device__ __forceinline__ void mbar_wait_hot(uint32_t bar, uint32_t par) {
  asm volatile(
    "{\n.reg .pred p;\n.reg .u32 n;\n"
    "mbarrier.try_wait.parity.shared::cta.b64 p, [%0], %1;\n"
    "@p bra W_DONE;\n"
    "mov.u32 n, 0;\n"
    "W_LOOP:\n"
    "mbarrier.try_wait.parity.shared::cta.b64 p, [%0], %1;\n"
    "@p bra W_DONE;\n"
    "add.u32 n, n, 1;\n"
    "setp.lt.u32 p, n, 0x400000;\n"
    "@p bra W_LOOP;\n"
    "trap;\n"
    "W_DONE:\n}" :: "r"(bar), "r"(par) : "memory");
}
__device__ __forceinline__ void tma_load(uint32_t dst, const CUtensorMap* m, uint32_t bar, int c0, int c1) {
  asm volatile("cp.async.bulk.tensor.2d.shared::cluster.global.mbarrier::complete_tx::bytes [%0], [%1, {%3, %4}], [%2];" :: "r"(dst), "l"(m), "r"(bar), "r"(c0), "r"(c1) : "memory");
}
#define TMA_MC(DIM) "@p cp.async.bulk.tensor." DIM ".shared::cluster.global.mbarrier::complete_tx::bytes.multicast::cluster "
template <int BYTES> __device__ __forceinline__ void load_one(uint32_t dst, const CUtensorMap* m, uint32_t bar, int c0, int c1) {
  asm volatile("{\n.reg .pred p;\nelect.sync _|p, 0xffffffff;\n@p mbarrier.arrive.expect_tx.shared::cta.b64 _, [%2], %6;\n"
               TMA_MC("2d") "[%0], [%1, {%3, %4}], [%2], %5;\n}"
               :: "r"(dst), "l"(m), "r"(bar), "r"(c0), "r"(c1), "h"((uint16_t)3), "n"(BYTES) : "memory");
}
__device__ __forceinline__ void load_w(uint32_t dst, const CUtensorMap* m, uint32_t bar, int c0, int c1) {
  asm volatile("{\n.reg .pred p;\nelect.sync _|p, 0xffffffff;\n@p mbarrier.arrive.expect_tx.shared::cta.b64 _, [%2], 16384;\n"
               TMA_MC("2d") "[%0], [%1, {%3, %4}], [%2], %5;\n" TMA_MC("2d") "[%6], [%1, {%7, %4}], [%2], %5;\n}"
               :: "r"(dst), "l"(m), "r"(bar), "r"(c0), "r"(c1), "h"((uint16_t)3), "r"(dst + 4096), "r"(c0 + 64) : "memory");
}
__device__ __forceinline__ void load_gu(uint32_t dst, const CUtensorMap* m, uint32_t bar, int c0, int c1, uint32_t bytes, int two) {
  asm volatile("{\n.reg .pred p, q;\nelect.sync _|p, 0xffffffff;\n@p mbarrier.arrive.expect_tx.shared::cta.b64 _, [%2], %8;\n"
               TMA_MC("3d") "[%0], [%1, {%3, %4, 0}], [%2], %5;\nsetp.ne.and.s32 p, %9, 0, p;\n" TMA_MC("3d") "[%6], [%1, {%7, %4, 0}], [%2], %5;\n}"
               :: "r"(dst), "l"(m), "r"(bar), "r"(c0), "r"(c1), "h"((uint16_t)3), "r"(dst + 4096), "r"(c0 + 32), "r"(bytes), "r"(two) : "memory");
}
__device__ __forceinline__ void tma_prefetch_e(const CUtensorMap* m, int c0, int c1) {
  asm volatile("{\n.reg .pred p;\nelect.sync _|p, 0xffffffff;\n@p cp.async.bulk.prefetch.tensor.2d.L2.global [%0, {%1, %2}];\n}" :: "l"(m), "r"(c0), "r"(c1) : "memory");
}
__device__ __forceinline__ void bulk_prefetch(const void* p, uint32_t bytes) {
  asm volatile("cp.async.bulk.prefetch.L2.global [%0], %1;" :: "l"(p), "r"(bytes) : "memory");
}
__device__ __forceinline__ void bulk_load_e(uint32_t dst, const void* src, uint32_t bytes, uint32_t bar) {
  asm volatile("{\n.reg .pred p;\nelect.sync _|p, 0xffffffff;\n@p cp.async.bulk.shared::cluster.global.mbarrier::complete_tx::bytes [%0], [%1], %3, [%2];\n}" :: "r"(dst), "l"(src), "r"(bar), "r"(bytes) : "memory");
}
__device__ __forceinline__ void bulk_store_e(void* dst, uint32_t src, uint32_t bytes) {
  asm volatile("{\n.reg .pred p;\nelect.sync _|p, 0xffffffff;\n@p cp.async.bulk.global.shared::cta.bulk_group [%0], [%1], %2;\n}" :: "l"(dst), "r"(src), "r"(bytes) : "memory");
}
__device__ __forceinline__ void bulk_store_wait() { asm volatile("cp.async.bulk.commit_group;\ncp.async.bulk.wait_group 0;" ::: "memory"); __syncwarp(); }
__device__ __forceinline__ void fence_async_smem() { asm volatile("fence.proxy.async.shared::cta;" ::: "memory"); }
__device__ __forceinline__ void bar_sync(int id, int n) { asm volatile("bar.sync %0, %1;" :: "r"(id), "r"(n) : "memory"); }
__device__ __forceinline__ void bar_arrive(int id, int n) { asm volatile("bar.arrive %0, %1;" :: "r"(id), "r"(n) : "memory"); }
__device__ __forceinline__ void wg_fence() { asm volatile("wgmma.fence.sync.aligned;" ::: "memory"); }
__device__ __forceinline__ void wg_commit() { asm volatile("wgmma.commit_group.sync.aligned;" ::: "memory"); }
template <int N> __device__ __forceinline__ void wg_wait() { asm volatile("wgmma.wait_group.sync.aligned %0;" :: "n"(N) : "memory"); }
template <int N> __device__ __forceinline__ void pin(float (&r)[N]) {
#pragma unroll
  for (int i = 0; i < N; i++) asm volatile("" : "+f"(r[i]) :: "memory");
}
template <int N> __device__ __forceinline__ void pin(uint32_t (&r)[N]) {
#pragma unroll
  for (int i = 0; i < N; i++) asm volatile("" : "+r"(r[i]) :: "memory");
}
__device__ __forceinline__ uint32_t make_desc(uint32_t addr, uint32_t lbo) { return ((addr & 0x3FFFF) >> 4) | ((lbo >> 4) << 16); }
__device__ __forceinline__ float ex2(float x) { float y; asm("ex2.approx.ftz.f32 %0, %1;" : "=f"(y) : "f"(x)); return y; }
__device__ __forceinline__ float tanh_fast(float x) { float y; asm("tanh.approx.f32 %0, %1;" : "=f"(y) : "f"(x)); return y; }
__device__ __forceinline__ uint32_t pack2(float lo, float hi) { uint32_t r; asm("cvt.rn.bf16x2.f32 %0, %1, %2;" : "=r"(r) : "f"(hi), "f"(lo)); return r; }
__device__ __forceinline__ float blo(uint32_t w) { return __uint_as_float(w << 16); }
__device__ __forceinline__ float bhi(uint32_t w) { return __uint_as_float(w & 0xffff0000u); }
__device__ __forceinline__ float bround(float x) { return blo(pack2(x, 0.f)); }
__device__ __forceinline__ uint32_t hfma2(uint32_t a, uint32_t b, uint32_t c) { uint32_t r; asm("fma.rn.bf16x2 %0, %1, %2, %3;" : "=r"(r) : "r"(a), "r"(b), "r"(c)); return r; }
__device__ __forceinline__ uint32_t one_plus(uint32_t w) { return pack2(1.f + blo(w), 1.f + bhi(w)); }
__device__ __forceinline__ void ldsm4(uint32_t addr, uint32_t& a, uint32_t& b, uint32_t& c, uint32_t& d) {
  asm volatile("ldmatrix.sync.aligned.m8n8.x4.shared.b16 {%0,%1,%2,%3}, [%4];" : "=r"(a), "=r"(b), "=r"(c), "=r"(d) : "r"(addr) : "memory");
}
__device__ __forceinline__ void stsm4(uint32_t addr, uint32_t a, uint32_t b, uint32_t c, uint32_t d) {
  asm volatile("stmatrix.sync.aligned.m8n8.x4.shared.b16 [%0], {%1,%2,%3,%4};" :: "r"(addr), "r"(a), "r"(b), "r"(c), "r"(d) : "memory");
}
__device__ __forceinline__ void sts128(uint32_t addr, uint32_t a, uint32_t b, uint32_t c, uint32_t d) {
  asm volatile("st.shared.v4.b32 [%0], {%1,%2,%3,%4};" :: "r"(addr), "r"(a), "r"(b), "r"(c), "r"(d) : "memory");
}
__device__ __forceinline__ uint4 lds128(uint32_t addr) {
  uint4 v; asm volatile("ld.shared.v4.b32 {%0,%1,%2,%3}, [%4];" : "=r"(v.x), "=r"(v.y), "=r"(v.z), "=r"(v.w) : "r"(addr) : "memory"); return v;
}
__device__ __forceinline__ void sts32(uint32_t addr, uint32_t v) { asm volatile("st.shared.b32 [%0], %1;" :: "r"(addr), "r"(v) : "memory"); }
__device__ __forceinline__ uint4 ldg_nc128(const void* p) {
  uint4 v; asm volatile("ld.global.nc.L2::128B.v4.b32 {%0,%1,%2,%3}, [%4];" : "=r"(v.x), "=r"(v.y), "=r"(v.z), "=r"(v.w) : "l"(p)); return v;
}
__device__ __forceinline__ uint32_t ldg_nc32(const void* p) { uint32_t v; asm volatile("ld.global.nc.b32 %0, [%1];" : "=r"(v) : "l"(p)); return v; }
#pragma nv_diag_suppress 177
template <int N> struct IC { static constexpr int v = N; __device__ constexpr operator int() const { return N; } };
template <int OFF> __device__ __forceinline__ void stg128o(void* p, uint32_t a, uint32_t b, uint32_t c, uint32_t d) {
  asm volatile("st.global.v4.b32 [%0 + %5], {%1,%2,%3,%4};" :: "l"(p), "r"(a), "r"(b), "r"(c), "r"(d), "n"(OFF) : "memory");
}
template <int OFF> __device__ __forceinline__ uint4 ldg_cg128o(const void* p) {
  uint4 v; asm volatile("ld.global.cg.v4.b32 {%0,%1,%2,%3}, [%4 + %5];" : "=r"(v.x), "=r"(v.y), "=r"(v.z), "=r"(v.w) : "l"(p), "n"(OFF) : "memory"); return v;
}
template <int I, int N, class F> __device__ __forceinline__ void static_for(F&& f) {
  if constexpr (I < N) { f(IC<I>()); static_for<I + 1, N>(f); }
}
template <int C> __device__ __forceinline__ void store_chunks(void* p, const uint32_t (&w)[32]) {
  stg128o<C * 512>(p, w[4 * C], w[4 * C + 1], w[4 * C + 2], w[4 * C + 3]);
  if constexpr (C < 7) store_chunks<C + 1>(p, w);
}
__device__ __forceinline__ void st_ll(unsigned long long* p, uint32_t val, uint32_t tag) {
  asm volatile("st.relaxed.gpu.global.b64 [%0], %1;" :: "l"(p), "l"(((unsigned long long)tag << 32) | val) : "memory");
}
__device__ __forceinline__ void flag_set(unsigned int* f, uint32_t tag) { asm volatile("st.release.gpu.global.u32 [%0], %1;" :: "l"(f), "r"(tag) : "memory"); }
__device__ __forceinline__ uint32_t flag_get(const unsigned int* f) { uint32_t v; asm volatile("ld.acquire.gpu.global.u32 %0, [%1];" : "=r"(v) : "l"(f) : "memory"); return v; }
__device__ __forceinline__ void trap_if(bool c) { asm volatile("{\n.reg .pred p;\nsetp.ne.u32 p, %0, 0;\n@p trap;\n}" :: "r"((uint32_t)c)); }
__device__ __forceinline__ float rcp_fast(float x) { float y; asm("rcp.approx.ftz.f32 %0, %1;" : "=f"(y) : "f"(x)); return y; }
__device__ __forceinline__ float sqrt_fast(float x) { float y; asm("sqrt.approx.ftz.f32 %0, %1;" : "=f"(y) : "f"(x)); return y; }
__device__ __forceinline__ float silu_bf(float x) { return bround(x * rcp_fast(1.f + ex2(-1.4426950408889634f * x))); }
__device__ __forceinline__ float ln_rstd(float mean, float ex2mean) { return rcp_fast(bround(sqrt_fast(bround(bround(fmaxf(ex2mean - mean * mean, 0.f)) + 1e-5f)))); }
__device__ __forceinline__ float xreduce8(float (&a)[8], int lane) {
#pragma unroll
  for (int i = 0; i < 4; i++) { const bool up = lane & 16; const float snd = up ? a[i] : a[i + 4], kp = up ? a[i + 4] : a[i]; a[i] = kp + __shfl_xor_sync(~0u, snd, 16); }
#pragma unroll
  for (int i = 0; i < 2; i++) { const bool up = lane & 8; const float snd = up ? a[i] : a[i + 2], kp = up ? a[i + 2] : a[i]; a[i] = kp + __shfl_xor_sync(~0u, snd, 8); }
  const bool up = lane & 4; const float snd = up ? a[0] : a[1], kp = up ? a[1] : a[0];
  const float r = kp + __shfl_xor_sync(~0u, snd, 4);
  return r + __shfl_xor_sync(~0u, r, 2);
}
__device__ __forceinline__ void mma16816(float& c0, float& c1, float& c2, float& c3, uint32_t a0, uint32_t a1, uint32_t a2, uint32_t a3, uint32_t b0, uint32_t b1) {
  asm("mma.sync.aligned.m16n8k16.row.col.f32.bf16.bf16.f32 {%0,%1,%2,%3}, {%4,%5,%6,%7}, {%8,%9}, {%0,%1,%2,%3};"
      : "+f"(c0), "+f"(c1), "+f"(c2), "+f"(c3) : "r"(a0), "r"(a1), "r"(a2), "r"(a3), "r"(b0), "r"(b1));
}

struct RedoArgs {
  float4 o[16];
  uint4 qp[8];
  float4 ml;
};
__device__ __noinline__ float2 redo_tile(RedoArgs& r, const __nv_bfloat16* kc, int tile) {
  const float cl2 = 0.08838834764831845f * 1.4426950408889634f;
  const int lane = threadIdx.x & 31;
  const uint32_t* kp = (const uint32_t*)(kc + (size_t)(tile * 128 + (lane >> 2)) * DH) + (lane & 3);
  float4 sr[16];
  float x0 = r.ml.x, x1 = r.ml.y;
#pragma unroll 1
  for (int j = 0; j < 16; j++) {
    float4 c = {0.f, 0.f, 0.f, 0.f};
#pragma unroll 1
    for (int kk = 0; kk < 8; kk++) {
      const uint4 a = r.qp[kk];
      mma16816(c.x, c.y, c.z, c.w, a.x, a.y, a.z, a.w, ldg_nc32(kp + j * 512 + kk * 8), ldg_nc32(kp + j * 512 + kk * 8 + 4));
    }
    sr[j] = c;
    x0 = fmaxf(x0, fmaf(fmaxf(c.x, c.y), cl2, BIAS)); x1 = fmaxf(x1, fmaf(fmaxf(c.z, c.w), cl2, BIAS));
  }
  x0 = fmaxf(x0, __shfl_xor_sync(~0u, x0, 1)); x1 = fmaxf(x1, __shfl_xor_sync(~0u, x1, 1));
  x0 = fmaxf(x0, __shfl_xor_sync(~0u, x0, 2)); x1 = fmaxf(x1, __shfl_xor_sync(~0u, x1, 2));
  const bool first = (tile & 15) == 0;
  const float a0 = first ? 1.f : ex2(r.ml.x - x0), a1 = first ? 1.f : ex2(r.ml.y - x1);
  r.ml = make_float4(x0, x1, r.ml.z * a0, r.ml.w * a1);
  float t0 = 0.f, t1 = 0.f;
#pragma unroll 1
  for (int j = 0; j < 16; j++) {
    const float4 c = sr[j], v = r.o[j];
    const float e0 = ex2(fmaf(c.x, cl2, -x0)), e1 = ex2(fmaf(c.y, cl2, -x0)), e2 = ex2(fmaf(c.z, cl2, -x1)), e3 = ex2(fmaf(c.w, cl2, -x1));
    t0 += e0 + e1; t1 += e2 + e3;
    ((uint2*)r.qp)[j] = make_uint2(pack2(e0, e1), pack2(e2, e3));
    r.o[j] = make_float4(v.x * a0, v.y * a0, v.z * a1, v.w * a1);
  }
  return make_float2(t0, t1);
}

__device__ __forceinline__ void wgmma_rs_n128_t1(float (&d)[64], uint32_t a0, uint32_t a1, uint32_t a2, uint32_t a3, uint32_t db, int scale_d) {
  asm volatile(
    "{\n.reg .pred p;\n.reg .b64 db;\nmov.b64 db, {%68, %70};\nsetp.ne.b32 p, %69, 0;\n"
    "wgmma.mma_async.sync.aligned.m64n128k16.f32.bf16.bf16 {"
    "%0, %1, %2, %3, %4, %5, %6, %7, %8, %9, %10, %11, %12, %13, %14, %15, "
    "%16, %17, %18, %19, %20, %21, %22, %23, %24, %25, %26, %27, %28, %29, %30, %31, "
    "%32, %33, %34, %35, %36, %37, %38, %39, %40, %41, %42, %43, %44, %45, %46, %47, "
    "%48, %49, %50, %51, %52, %53, %54, %55, %56, %57, %58, %59, %60, %61, %62, %63"
    "}, {%64, %65, %66, %67}, db, p, 1, 1, 1;\n}\n"
    : "+f"(d[0]), "+f"(d[1]), "+f"(d[2]), "+f"(d[3]), "+f"(d[4]), "+f"(d[5]), "+f"(d[6]), "+f"(d[7]),
      "+f"(d[8]), "+f"(d[9]), "+f"(d[10]), "+f"(d[11]), "+f"(d[12]), "+f"(d[13]), "+f"(d[14]), "+f"(d[15]),
      "+f"(d[16]), "+f"(d[17]), "+f"(d[18]), "+f"(d[19]), "+f"(d[20]), "+f"(d[21]), "+f"(d[22]), "+f"(d[23]),
      "+f"(d[24]), "+f"(d[25]), "+f"(d[26]), "+f"(d[27]), "+f"(d[28]), "+f"(d[29]), "+f"(d[30]), "+f"(d[31]),
      "+f"(d[32]), "+f"(d[33]), "+f"(d[34]), "+f"(d[35]), "+f"(d[36]), "+f"(d[37]), "+f"(d[38]), "+f"(d[39]),
      "+f"(d[40]), "+f"(d[41]), "+f"(d[42]), "+f"(d[43]), "+f"(d[44]), "+f"(d[45]), "+f"(d[46]), "+f"(d[47]),
      "+f"(d[48]), "+f"(d[49]), "+f"(d[50]), "+f"(d[51]), "+f"(d[52]), "+f"(d[53]), "+f"(d[54]), "+f"(d[55]),
      "+f"(d[56]), "+f"(d[57]), "+f"(d[58]), "+f"(d[59]), "+f"(d[60]), "+f"(d[61]), "+f"(d[62]), "+f"(d[63])
    : "r"(a0), "r"(a1), "r"(a2), "r"(a3), "r"(db), "r"(scale_d), "r"(0x40000040u));
}
__device__ __forceinline__ void wgmma_ss_n128_t1(float (&d)[64], uint32_t da, uint32_t db, int scale_d, uint32_t db_hi = 0x40000040u) {
  asm volatile(
    "{\n.reg .pred p;\n.reg .b64 da, db;\nmov.b64 da, {%64, %67};\nmov.b64 db, {%65, %68};\nsetp.ne.b32 p, %66, 0;\n"
    "wgmma.mma_async.sync.aligned.m64n128k16.f32.bf16.bf16 {"
    "%0, %1, %2, %3, %4, %5, %6, %7, %8, %9, %10, %11, %12, %13, %14, %15, "
    "%16, %17, %18, %19, %20, %21, %22, %23, %24, %25, %26, %27, %28, %29, %30, %31, "
    "%32, %33, %34, %35, %36, %37, %38, %39, %40, %41, %42, %43, %44, %45, %46, %47, "
    "%48, %49, %50, %51, %52, %53, %54, %55, %56, %57, %58, %59, %60, %61, %62, %63"
    "}, da, db, p, 1, 1, 0, 1;\n}\n"
    : "+f"(d[0]), "+f"(d[1]), "+f"(d[2]), "+f"(d[3]), "+f"(d[4]), "+f"(d[5]), "+f"(d[6]), "+f"(d[7]),
      "+f"(d[8]), "+f"(d[9]), "+f"(d[10]), "+f"(d[11]), "+f"(d[12]), "+f"(d[13]), "+f"(d[14]), "+f"(d[15]),
      "+f"(d[16]), "+f"(d[17]), "+f"(d[18]), "+f"(d[19]), "+f"(d[20]), "+f"(d[21]), "+f"(d[22]), "+f"(d[23]),
      "+f"(d[24]), "+f"(d[25]), "+f"(d[26]), "+f"(d[27]), "+f"(d[28]), "+f"(d[29]), "+f"(d[30]), "+f"(d[31]),
      "+f"(d[32]), "+f"(d[33]), "+f"(d[34]), "+f"(d[35]), "+f"(d[36]), "+f"(d[37]), "+f"(d[38]), "+f"(d[39]),
      "+f"(d[40]), "+f"(d[41]), "+f"(d[42]), "+f"(d[43]), "+f"(d[44]), "+f"(d[45]), "+f"(d[46]), "+f"(d[47]),
      "+f"(d[48]), "+f"(d[49]), "+f"(d[50]), "+f"(d[51]), "+f"(d[52]), "+f"(d[53]), "+f"(d[54]), "+f"(d[55]),
      "+f"(d[56]), "+f"(d[57]), "+f"(d[58]), "+f"(d[59]), "+f"(d[60]), "+f"(d[61]), "+f"(d[62]), "+f"(d[63])
    : "r"(da), "r"(db), "r"(scale_d), "r"(0x40000040u), "r"(db_hi));
}
__device__ __forceinline__ void wgmma_ss_n256_t1(float (&d)[128], uint32_t da, uint32_t db, int scale_d, uint32_t db_hi = 0x40000040u) {
  asm volatile(
    "{\n.reg .pred p;\n.reg .b64 da, db;\nmov.b64 da, {%128, %131};\nmov.b64 db, {%129, %132};\nsetp.ne.b32 p, %130, 0;\n"
    "wgmma.mma_async.sync.aligned.m64n256k16.f32.bf16.bf16 {"
    "%0, %1, %2, %3, %4, %5, %6, %7, %8, %9, %10, %11, %12, %13, %14, %15, "
    "%16, %17, %18, %19, %20, %21, %22, %23, %24, %25, %26, %27, %28, %29, %30, %31, "
    "%32, %33, %34, %35, %36, %37, %38, %39, %40, %41, %42, %43, %44, %45, %46, %47, "
    "%48, %49, %50, %51, %52, %53, %54, %55, %56, %57, %58, %59, %60, %61, %62, %63, "
    "%64, %65, %66, %67, %68, %69, %70, %71, %72, %73, %74, %75, %76, %77, %78, %79, "
    "%80, %81, %82, %83, %84, %85, %86, %87, %88, %89, %90, %91, %92, %93, %94, %95, "
    "%96, %97, %98, %99, %100, %101, %102, %103, %104, %105, %106, %107, %108, %109, %110, %111, "
    "%112, %113, %114, %115, %116, %117, %118, %119, %120, %121, %122, %123, %124, %125, %126, %127"
    "}, da, db, p, 1, 1, 0, 1;\n}\n"
    : "+f"(d[0]), "+f"(d[1]), "+f"(d[2]), "+f"(d[3]), "+f"(d[4]), "+f"(d[5]), "+f"(d[6]), "+f"(d[7]),
      "+f"(d[8]), "+f"(d[9]), "+f"(d[10]), "+f"(d[11]), "+f"(d[12]), "+f"(d[13]), "+f"(d[14]), "+f"(d[15]),
      "+f"(d[16]), "+f"(d[17]), "+f"(d[18]), "+f"(d[19]), "+f"(d[20]), "+f"(d[21]), "+f"(d[22]), "+f"(d[23]),
      "+f"(d[24]), "+f"(d[25]), "+f"(d[26]), "+f"(d[27]), "+f"(d[28]), "+f"(d[29]), "+f"(d[30]), "+f"(d[31]),
      "+f"(d[32]), "+f"(d[33]), "+f"(d[34]), "+f"(d[35]), "+f"(d[36]), "+f"(d[37]), "+f"(d[38]), "+f"(d[39]),
      "+f"(d[40]), "+f"(d[41]), "+f"(d[42]), "+f"(d[43]), "+f"(d[44]), "+f"(d[45]), "+f"(d[46]), "+f"(d[47]),
      "+f"(d[48]), "+f"(d[49]), "+f"(d[50]), "+f"(d[51]), "+f"(d[52]), "+f"(d[53]), "+f"(d[54]), "+f"(d[55]),
      "+f"(d[56]), "+f"(d[57]), "+f"(d[58]), "+f"(d[59]), "+f"(d[60]), "+f"(d[61]), "+f"(d[62]), "+f"(d[63]),
      "+f"(d[64]), "+f"(d[65]), "+f"(d[66]), "+f"(d[67]), "+f"(d[68]), "+f"(d[69]), "+f"(d[70]), "+f"(d[71]),
      "+f"(d[72]), "+f"(d[73]), "+f"(d[74]), "+f"(d[75]), "+f"(d[76]), "+f"(d[77]), "+f"(d[78]), "+f"(d[79]),
      "+f"(d[80]), "+f"(d[81]), "+f"(d[82]), "+f"(d[83]), "+f"(d[84]), "+f"(d[85]), "+f"(d[86]), "+f"(d[87]),
      "+f"(d[88]), "+f"(d[89]), "+f"(d[90]), "+f"(d[91]), "+f"(d[92]), "+f"(d[93]), "+f"(d[94]), "+f"(d[95]),
      "+f"(d[96]), "+f"(d[97]), "+f"(d[98]), "+f"(d[99]), "+f"(d[100]), "+f"(d[101]), "+f"(d[102]), "+f"(d[103]),
      "+f"(d[104]), "+f"(d[105]), "+f"(d[106]), "+f"(d[107]), "+f"(d[108]), "+f"(d[109]), "+f"(d[110]), "+f"(d[111]),
      "+f"(d[112]), "+f"(d[113]), "+f"(d[114]), "+f"(d[115]), "+f"(d[116]), "+f"(d[117]), "+f"(d[118]), "+f"(d[119]),
      "+f"(d[120]), "+f"(d[121]), "+f"(d[122]), "+f"(d[123]), "+f"(d[124]), "+f"(d[125]), "+f"(d[126]), "+f"(d[127])
    : "r"(da), "r"(db), "r"(scale_d), "r"(0x40000040u), "r"(db_hi));
}
__device__ __forceinline__ void wgmma_ss_n192_t1(float (&d)[96], uint32_t da, uint32_t db, int scale_d, uint32_t db_hi = 0x40000040u) {
  asm volatile(
    "{\n.reg .pred p;\n.reg .b64 da, db;\nmov.b64 da, {%96, %99};\nmov.b64 db, {%97, %100};\nsetp.ne.b32 p, %98, 0;\n"
    "wgmma.mma_async.sync.aligned.m64n192k16.f32.bf16.bf16 {"
    "%0, %1, %2, %3, %4, %5, %6, %7, %8, %9, %10, %11, %12, %13, %14, %15, "
    "%16, %17, %18, %19, %20, %21, %22, %23, %24, %25, %26, %27, %28, %29, %30, %31, "
    "%32, %33, %34, %35, %36, %37, %38, %39, %40, %41, %42, %43, %44, %45, %46, %47, "
    "%48, %49, %50, %51, %52, %53, %54, %55, %56, %57, %58, %59, %60, %61, %62, %63, "
    "%64, %65, %66, %67, %68, %69, %70, %71, %72, %73, %74, %75, %76, %77, %78, %79, "
    "%80, %81, %82, %83, %84, %85, %86, %87, %88, %89, %90, %91, %92, %93, %94, %95"
    "}, da, db, p, 1, 1, 0, 1;\n}\n"
    : "+f"(d[0]), "+f"(d[1]), "+f"(d[2]), "+f"(d[3]), "+f"(d[4]), "+f"(d[5]), "+f"(d[6]), "+f"(d[7]),
      "+f"(d[8]), "+f"(d[9]), "+f"(d[10]), "+f"(d[11]), "+f"(d[12]), "+f"(d[13]), "+f"(d[14]), "+f"(d[15]),
      "+f"(d[16]), "+f"(d[17]), "+f"(d[18]), "+f"(d[19]), "+f"(d[20]), "+f"(d[21]), "+f"(d[22]), "+f"(d[23]),
      "+f"(d[24]), "+f"(d[25]), "+f"(d[26]), "+f"(d[27]), "+f"(d[28]), "+f"(d[29]), "+f"(d[30]), "+f"(d[31]),
      "+f"(d[32]), "+f"(d[33]), "+f"(d[34]), "+f"(d[35]), "+f"(d[36]), "+f"(d[37]), "+f"(d[38]), "+f"(d[39]),
      "+f"(d[40]), "+f"(d[41]), "+f"(d[42]), "+f"(d[43]), "+f"(d[44]), "+f"(d[45]), "+f"(d[46]), "+f"(d[47]),
      "+f"(d[48]), "+f"(d[49]), "+f"(d[50]), "+f"(d[51]), "+f"(d[52]), "+f"(d[53]), "+f"(d[54]), "+f"(d[55]),
      "+f"(d[56]), "+f"(d[57]), "+f"(d[58]), "+f"(d[59]), "+f"(d[60]), "+f"(d[61]), "+f"(d[62]), "+f"(d[63]),
      "+f"(d[64]), "+f"(d[65]), "+f"(d[66]), "+f"(d[67]), "+f"(d[68]), "+f"(d[69]), "+f"(d[70]), "+f"(d[71]),
      "+f"(d[72]), "+f"(d[73]), "+f"(d[74]), "+f"(d[75]), "+f"(d[76]), "+f"(d[77]), "+f"(d[78]), "+f"(d[79]),
      "+f"(d[80]), "+f"(d[81]), "+f"(d[82]), "+f"(d[83]), "+f"(d[84]), "+f"(d[85]), "+f"(d[86]), "+f"(d[87]),
      "+f"(d[88]), "+f"(d[89]), "+f"(d[90]), "+f"(d[91]), "+f"(d[92]), "+f"(d[93]), "+f"(d[94]), "+f"(d[95])
    : "r"(da), "r"(db), "r"(scale_d), "r"(0x40000040u), "r"(db_hi));
}
__device__ __forceinline__ void wgmma64_rs_n128_t0(float (&d)[64], uint32_t a0, uint32_t a1, uint32_t a2, uint32_t a3, uint64_t db, int scale_d) {
  asm volatile(
    "{\n.reg .pred p;\nsetp.ne.b32 p, %69, 0;\n"
    "wgmma.mma_async.sync.aligned.m64n128k16.f32.bf16.bf16 {"
    "%0, %1, %2, %3, %4, %5, %6, %7, %8, %9, %10, %11, %12, %13, %14, %15, "
    "%16, %17, %18, %19, %20, %21, %22, %23, %24, %25, %26, %27, %28, %29, %30, %31, "
    "%32, %33, %34, %35, %36, %37, %38, %39, %40, %41, %42, %43, %44, %45, %46, %47, "
    "%48, %49, %50, %51, %52, %53, %54, %55, %56, %57, %58, %59, %60, %61, %62, %63"
    "}, {%64, %65, %66, %67}, %68, p, 1, 1, 0;\n}\n"
    : "+f"(d[0]), "+f"(d[1]), "+f"(d[2]), "+f"(d[3]), "+f"(d[4]), "+f"(d[5]), "+f"(d[6]), "+f"(d[7]),
      "+f"(d[8]), "+f"(d[9]), "+f"(d[10]), "+f"(d[11]), "+f"(d[12]), "+f"(d[13]), "+f"(d[14]), "+f"(d[15]),
      "+f"(d[16]), "+f"(d[17]), "+f"(d[18]), "+f"(d[19]), "+f"(d[20]), "+f"(d[21]), "+f"(d[22]), "+f"(d[23]),
      "+f"(d[24]), "+f"(d[25]), "+f"(d[26]), "+f"(d[27]), "+f"(d[28]), "+f"(d[29]), "+f"(d[30]), "+f"(d[31]),
      "+f"(d[32]), "+f"(d[33]), "+f"(d[34]), "+f"(d[35]), "+f"(d[36]), "+f"(d[37]), "+f"(d[38]), "+f"(d[39]),
      "+f"(d[40]), "+f"(d[41]), "+f"(d[42]), "+f"(d[43]), "+f"(d[44]), "+f"(d[45]), "+f"(d[46]), "+f"(d[47]),
      "+f"(d[48]), "+f"(d[49]), "+f"(d[50]), "+f"(d[51]), "+f"(d[52]), "+f"(d[53]), "+f"(d[54]), "+f"(d[55]),
      "+f"(d[56]), "+f"(d[57]), "+f"(d[58]), "+f"(d[59]), "+f"(d[60]), "+f"(d[61]), "+f"(d[62]), "+f"(d[63])
    : "r"(a0), "r"(a1), "r"(a2), "r"(a3), "l"(db), "r"(scale_d));
}
__device__ __forceinline__ void wgmma64_rs_n128_t1(float (&d)[64], uint32_t a0, uint32_t a1, uint32_t a2, uint32_t a3, uint64_t db, int scale_d) {
  asm volatile(
    "{\n.reg .pred p;\nsetp.ne.b32 p, %69, 0;\n"
    "wgmma.mma_async.sync.aligned.m64n128k16.f32.bf16.bf16 {"
    "%0, %1, %2, %3, %4, %5, %6, %7, %8, %9, %10, %11, %12, %13, %14, %15, "
    "%16, %17, %18, %19, %20, %21, %22, %23, %24, %25, %26, %27, %28, %29, %30, %31, "
    "%32, %33, %34, %35, %36, %37, %38, %39, %40, %41, %42, %43, %44, %45, %46, %47, "
    "%48, %49, %50, %51, %52, %53, %54, %55, %56, %57, %58, %59, %60, %61, %62, %63"
    "}, {%64, %65, %66, %67}, %68, p, 1, 1, 1;\n}\n"
    : "+f"(d[0]), "+f"(d[1]), "+f"(d[2]), "+f"(d[3]), "+f"(d[4]), "+f"(d[5]), "+f"(d[6]), "+f"(d[7]),
      "+f"(d[8]), "+f"(d[9]), "+f"(d[10]), "+f"(d[11]), "+f"(d[12]), "+f"(d[13]), "+f"(d[14]), "+f"(d[15]),
      "+f"(d[16]), "+f"(d[17]), "+f"(d[18]), "+f"(d[19]), "+f"(d[20]), "+f"(d[21]), "+f"(d[22]), "+f"(d[23]),
      "+f"(d[24]), "+f"(d[25]), "+f"(d[26]), "+f"(d[27]), "+f"(d[28]), "+f"(d[29]), "+f"(d[30]), "+f"(d[31]),
      "+f"(d[32]), "+f"(d[33]), "+f"(d[34]), "+f"(d[35]), "+f"(d[36]), "+f"(d[37]), "+f"(d[38]), "+f"(d[39]),
      "+f"(d[40]), "+f"(d[41]), "+f"(d[42]), "+f"(d[43]), "+f"(d[44]), "+f"(d[45]), "+f"(d[46]), "+f"(d[47]),
      "+f"(d[48]), "+f"(d[49]), "+f"(d[50]), "+f"(d[51]), "+f"(d[52]), "+f"(d[53]), "+f"(d[54]), "+f"(d[55]),
      "+f"(d[56]), "+f"(d[57]), "+f"(d[58]), "+f"(d[59]), "+f"(d[60]), "+f"(d[61]), "+f"(d[62]), "+f"(d[63])
    : "r"(a0), "r"(a1), "r"(a2), "r"(a3), "l"(db), "r"(scale_d));
}


constexpr int B_PP = 1;
constexpr int B_CONS = 3;
constexpr int B_WG = 4;
constexpr int B_AUX = 6;
constexpr int B_LAG = 10;
constexpr int B_X = 7;
constexpr int B_PUB = 8;

template <bool SWP>
__global__ void __cluster_dims__(2, 1, 1) __launch_bounds__(384, 1)
fused_kernel(Scratch* __restrict__ scr, const __nv_bfloat16* __restrict__ cvec, const __nv_bfloat16* __restrict__ wmod,
             const __nv_bfloat16* __restrict__ x, const __nv_bfloat16* __restrict__ kc, __nv_bfloat16* __restrict__ out,
             const __nv_bfloat16* __restrict__ wo, const __nv_bfloat16* __restrict__ wg, const __nv_bfloat16* __restrict__ wu,
             const __nv_bfloat16* __restrict__ wd, const __nv_bfloat16* __restrict__ vc, const __grid_constant__ Maps mp) {
  extern __shared__ __align__(1024) uint8_t sm_raw[];
  const uint32_t sb = smem_u32(sm_raw);
  const int tid = threadIdx.x, lane = tid & 31;
  const int warp = __shfl_sync(~0u, tid >> 5, 0);
  const int b = blockIdx.x;
  const uint32_t rank = b & 1;
  const int g = b >> 4;
  const int rt = b & 15;
  const int rtd = (rt & 14) | (g & 1), cbd = g >> 1;
  auto FULL = [&](int h) { return sb + OFF_BAR + 8 * h; };
  auto EMPTY = [&](int h) { return sb + OFF_BAR + 112 + 8 * h; };
  auto AFULL = [&](int s) { return sb + OFF_BAR + 200 + 8 * s; };
  auto AEMPTY = [&](int s) { return sb + OFF_BAR + 232 + 8 * s; };
  auto XFULL = [&](int r) { return sb + OFF_BAR + 288 + 8 * r; };
  const uint32_t MODFULL = sb + OFF_BAR + 320;

  if (warp < 4) {
    asm volatile("setmaxnreg.dec.sync.aligned.u32 %0;" :: "n"(PROD_REGS));
    if (tid == 0) {
      trap_if(sb & 1023);
#pragma unroll
      for (int i = 40; i >= 0; i--) mbar_init(sb + OFF_BAR + 8 * i, i == 40 ? 64 : (i >= 14 && i < 28) || (i >= 32 && i < 36) ? 16 : 1);
      asm volatile("fence.mbarrier_init.release.cluster;" ::: "memory");
      fence_async_smem();
    }
    __syncwarp();
    asm volatile("barrier.cluster.arrive.relaxed.aligned;" ::: "memory");
    if (warp == 0) {
      if (lane < 4) mbar_expect_tx(XFULL(lane), SLOT);
      __syncwarp();
      tma_load(sb + (lane & 7) * HALF + (lane >> 3) * 4096, &mp.x, XFULL(lane >> 3), (lane & 7) * 64, rt * 128 + (lane >> 3) * 32);
    }
    uint32_t tag = 0;
    if (warp < 2) asm volatile("ld.relaxed.gpu.global.u32 %0, [%1];" : "=r"(tag) : "l"(&scr->sync.epoch) : "memory");
    asm volatile("barrier.cluster.wait.aligned;" ::: "memory");
    tag += 1;
    if (warp != 2) {
      if (warp < 2) {
        const int j = tid;
        const unsigned long long* src = &scr->sync.modll[((b >> 1) & 3) * 512 + 2 * j];
        uint4 pk[4];
        int n = 0;
        mbar_wait(XFULL(1), 0);
        while (true) {
#pragma unroll
          for (int i = 0; i < 4; i++) asm volatile("ld.relaxed.gpu.global.v2.b64 {%0, %1}, [%2];" : "=l"(*(unsigned long long*)&pk[i].x), "=l"(*(unsigned long long*)&pk[i].z) : "l"(src + i * 128) : "memory");
          uint32_t bad = 0;
#pragma unroll
          for (int i = 0; i < 4; i++) bad |= (pk[i].y ^ tag) | (pk[i].w ^ tag);
          if (__all_sync(~0u, bad == 0)) break;
          trap_if(++n > (1 << 24));
        }
#pragma unroll
        for (int i = 0; i < 4; i++)
          asm volatile("st.shared.v2.b32 [%0], {%1, %2};" :: "r"(sb + OFF_MODSM + i * 512 + j * 8), "r"(i < 2 ? pk[i].x : one_plus(pk[i].x)), "r"(i < 2 ? pk[i].z : one_plus(pk[i].z)) : "memory");
        asm volatile("mbarrier.arrive.shared::cta.b64 _, [%0];" :: "r"(MODFULL) : "memory");
      }
      bar_sync(B_AUX, 96);
    }
    if (warp == 3) {
      mbar_wait(AFULL(4), 0);
      float a[8];
#pragma unroll
      for (int i = 0; i < 8; i++) a[i] = 0.f;
#pragma unroll 2
      for (int k = lane >> 1; k < 512; k += 16) {
        const uint4 w = ldg_nc128(wmod + (size_t)k * 3072 + 1024 + b * 16 + (lane & 1) * 8);
        const float sc = silu_bf(__bfloat162float(cvec[k]));
        a[0] += sc * blo(w.x); a[1] += sc * bhi(w.x); a[2] += sc * blo(w.y); a[3] += sc * bhi(w.y);
        a[4] += sc * blo(w.z); a[5] += sc * bhi(w.z); a[6] += sc * blo(w.w); a[7] += sc * bhi(w.w);
      }
      const float r = xreduce8(a, lane);
      uint32_t w = pack2(r, __shfl_xor_sync(~0u, r, 4));
      if ((b >> 5) == 2) w = one_plus(w);
      if ((lane & 6) == 0) scr->sync.late[(b >> 5) * 256 + (b & 7) * 32 + (lane >> 3) * 8 + ((b >> 3) & 3) * 2 + (lane & 1)] = w;
      __syncwarp();
      if (lane == 0) asm volatile("red.release.gpu.global.add.u32 [%0], 1;" :: "l"(&scr->sync.late_cnt) : "memory");
      mbar_wait(XFULL(2), 1);
      if (lane < 4) bulk_prefetch((const uint8_t*)(lane == 0 ? wo : lane == 1 ? wg : lane == 2 ? wu : wd) + (size_t)b * (lane ? 14336 : 32768), lane ? 14336 : 32768);
    } else if (warp == 2) {
      uint32_t pe = 0x3f00;
      auto wait_empty = [&](int h) { mbar_wait(EMPTY(h), (pe >> h) & 1); pe ^= 1u << h; };
      const uint32_t wdst = sb + rank * 8192;
      auto arrive = [&](uint32_t bar) { asm volatile("{\n.reg .pred p;\nelect.sync _|p, 0xffffffff;\n@p mbarrier.arrive.shared::cta.b64 _, [%0];\n}" :: "r"(bar) : "memory"); };
      arrive(AFULL(3));
      mbar_wait(XFULL(3), 0);
      int h6 = 8;
#pragma unroll 1
      for (int i = 0; i < 32; i++) {
        wait_empty(h6);
        load_w(wdst + h6 * HALF, &mp.wq, FULL(h6), g * 512 + (i < 16 ? 256 : 0) + rank * 128, (i & 15) * 32);
        if (i >= 8 && i < 24) asm volatile("{\n.reg .pred p;\nelect.sync _|p, 0xffffffff;\n@p cp.async.bulk.prefetch.L2.global [%0], 4096;\n}" :: "l"(((i & 1) ? vc : kc) + (size_t)(g * SEQ + rt * 128) * DH + ((i - 8) >> 1) * 2048) : "memory");
        if (i == 5) {
#pragma unroll 1
          for (int j = 0; j < 8; j++) tma_prefetch_e(&mp.wq, g * 512 + (rt < 8 ? 256 : 0) + (j & 3) * 64, (rt & 7) * 64 + (j >> 2) * 32);
        }
        h6 = h6 == 13 ? 8 : h6 + 1;
      }
#pragma unroll 1
      for (int u = 0; u < 128; u++) {
        const int isv = (u != 0 && (u & 1) == 0) || u == 127, t = u == 127 ? 63 : isv ? (u >> 1) - 1 : (u + 1) >> 1;
        const int s = isv ? 4 - (t & 1) : 5 + (t & 1);
        mbar_wait(AEMPTY(s), t >> 1);
        if (u == 112) arrive(XFULL(2));
        load_one<SLOT>(sb + s * SLOT + rank * HALF, isv ? &mp.v : &mp.k, AFULL(s), rank * 64, g * SEQ + (t & 15) * 128);
      }
#pragma unroll 1
      for (int i = 0; i < 32; i++) {
        const int h = (0x7698dcba >> ((i & 7) * 4)) & 15;
        if (i < 8) mbar_wait(AEMPTY(h >> 1), 0); else wait_empty(h);
        if (i == 0) arrive(AFULL(5));
        load_one<HALF>(wdst + h * HALF, &mp.wo, FULL(h), (i >> 3) * 128 + rank * 64, g * 512 + (i & 7) * 64);
      }
      mbar_wait(XFULL(0), 1);
      h6 = 10;
#pragma unroll 1
      for (int i = 0; i < 32; i++) {
        wait_empty(h6);
        load_gu(wdst + h6 * HALF, &mp.gu, FULL(h6), g * FS + (i >> 4) * 128 + rank * 64, (i & 15) * 32, i < 16 ? HALF : 12288, i < 16 || rank == 0);
        h6 = h6 == 13 ? 8 : h6 + 1;
      }
    } else if (warp == 1) {
#pragma unroll 1
      for (int i = 0; i < 6; i++) asm volatile("prefetch.tensormap [%0];" :: "l"(&mp.wq + i) : "memory");
#pragma unroll 1
      for (int stage = 0; stage < 5; stage++) {
        bar_sync(B_PUB + (stage & 1), stage < 4 ? 320 : 288);
        if (stage == 2) {
#pragma unroll 1
          for (int k = 0; k < 8; k++) bulk_store_e(scr->h2 + (rt * 8 + k) * 1024 + g * 128, sb + k * 2048, 2048);
          bulk_store_wait();
        }
        if (lane == 0) flag_set(&scr->sync.flag[(stage * 16 + rt) * 32 + g], tag);
      }
    } else {
      int n = 0;
      while ((int)(flag_get(&scr->sync.late_cnt) - tag * 128) < 0) { __nanosleep(200); trap_if(++n > (1 << 22)); }
#pragma unroll 1
      for (int stage = 0; stage < 3; stage++) {
        const int tail = stage == 1;
        const uint32_t bar = tail ? XFULL(0) : FULL(0);
        const uint4* src = stage == 2 ? scr->h2 + rt * 8192 : scr->part + (size_t)((rt * 8 + g) * 2 + tail) * 4096;
        const unsigned int* fl = &scr->sync.flag[(stage * 16 + rt) * 32];
        const int sh = stage == 2;
        uint32_t todo = 0xff;
        bool armed = false;
        n = 0;
        bar_sync(B_PUB + (stage & 1), 320);
        while (todo) {
          uint32_t rdy = __ballot_sync(~0u, flag_get(fl + (lane & 7)) == tag) & todo;
          if (!tail && rdy != 0xff) rdy = 0;
          todo ^= rdy;
          if (rdy) {
            asm volatile("fence.proxy.async.global;" ::: "memory");
            if (!armed) {
              armed = true;
              if (stage == 0) bar_sync(B_X, 288);
              if (lane < (sh ? 8 : 1)) mbar_expect_tx(bar + lane * 8, sh ? HALF : 65536);
              __syncwarp();
            }
            for (; rdy; rdy &= rdy - 1) {
              const int sg = __ffs(rdy) - 1;
              bulk_load_e(sb + tail * 65536 + (sg << (13 + sh)), src + (sg << (9 + sh)), 8192 << sh, bar + sh * sg * 8);
            }
          }
          trap_if(++n > (1 << 24));
        }
      }
      if (lane == 0) mbar_expect_tx(XFULL(1), HALF);
      bar_sync(B_PUB + 1, 320);
      int h = 0;
#pragma unroll 1
      for (int ii = -2; ii < 14; ii++) {
        const int i = ii < 0 ? ii + 2 : ii;
        const int wts = ii < 0 || ii >= 2;
        if ((ii & 7) == 0) {
          n = 0;
          while (!__all_sync(~0u, flag_get(&scr->sync.flag[((3 + (i >> 3)) * 16 + rtd) * 32 + (i ? rank * 4 + (lane & 3) : lane & 7)]) == tag)) trap_if(++n > (1 << 24));
          asm volatile("fence.proxy.async.global;" ::: "memory");
          if (ii == 0) h = 0;
        }
        int kt = rank * 28 + (i < 8 ? (i >> 1) * 7 + (i & 1) * 2 : i < 12 ? i * 7 - 52 : i * 14 - 162);
#pragma unroll
        for (int u = 0; u < 2; u++) {
          if (wts) mbar_wait(EMPTY(h + u), (0x0fc0 >> h) ^ (i >= 7));
          asm volatile("{\n.reg .pred p, pa, pb;\nelect.sync _|p, 0xffffffff;\nsetp.ne.and.s32 pb, %9, 0, p;\nsetp.ge.and.s32 pa, %10, 0, p;\n"
                       "@pb mbarrier.arrive.expect_tx.shared::cta.b64 _, [%2], 16384;\n"
                       "@pa cp.async.bulk.shared::cluster.global.mbarrier::complete_tx::bytes [%0], [%1], 8192, [%2];\n"
                       "@pb cp.async.bulk.tensor.2d.shared::cluster.global.mbarrier::complete_tx::bytes [%3], [%4, {%5, %6}], [%2];\n"
                       "@pb cp.async.bulk.tensor.2d.shared::cluster.global.mbarrier::complete_tx::bytes [%7], [%4, {%8, %6}], [%2];\n}"
                       :: "r"(sb + (h + u) * HALF), "l"(scr->act + rtd * 28672 + kt * 512), "r"(FULL(h + u)),
                          "r"(sb + (h + u) * HALF + 8192), "l"(&mp.wd), "r"(cbd * 128 + rank * 64), "r"(kt * 32), "r"(sb + (h + u) * HALF + 12288), "r"(cbd * 128 + 64 - rank * 64),
                          "r"(wts), "r"(ii) : "memory");
          kt += i < 12 ? 1 : 7;
        }
        h = h == 4 ? 8 : h == 12 ? 6 : h == 6 ? 0 : h + 2;
      }
    }
  } else {
    asm volatile("barrier.cluster.arrive.relaxed.aligned;" ::: "memory");
    asm volatile("setmaxnreg.inc.sync.aligned.u32 %0;" :: "n"(CONS_REGS));
    const int ct = tid - 128, wid = warp - 4, cw = wid >> 2;
    auto release = [&](int h) {
      asm volatile("{\n.reg .pred p;\n.reg .b32 a, c;\nelect.sync _|p, 0xffffffff;\nmapa.shared::cluster.u32 a, %0, 0;\nmapa.shared::cluster.u32 c, %0, 1;\n"
                   "@p mbarrier.arrive.shared::cluster.b64 _, [a];\n@p mbarrier.arrive.shared::cluster.b64 _, [c];\n}" :: "r"(EMPTY(h)) : "memory");
    };
    auto release_a = [&](int s) { release(15 + s); };
    uint32_t pf = 0;
    auto wait_full = [&](int h) { mbar_wait(FULL(h), (pf >> h) & 1); pf ^= 1u << h; };
    const uint32_t frag_row = wid * 16 + (lane & 15);
    const uint32_t fa0 = sb + frag_row * 128 + (((lane >> 4) ^ (lane & 7)) << 4);
    auto frag_addr = [&](int slot, int kk) { return (fa0 ^ ((kk & 3) << 5)) + slot * SLOT + (kk >> 2) * HALF; };
    uint32_t tag;
    uint32_t nm, rhl;

    {
      asm volatile("ld.relaxed.gpu.global.u32 %0, [%1];" : "=r"(tag) : "l"(&scr->sync.epoch) : "memory");
      const uint4 w0 = ldg_nc128(wmod + (size_t)ct * 3072 + b * 8), w1 = ldg_nc128(wmod + (size_t)(ct + 256) * 3072 + b * 8);
      const float c0 = __bfloat162float(cvec[ct]), c1 = __bfloat162float(cvec[ct + 256]);
      asm volatile("barrier.cluster.wait.aligned;" ::: "memory");
      tag += 1;
      {
        const float s0 = silu_bf(c0), s1 = silu_bf(c1);
        float a[8] = {s0 * blo(w0.x) + s1 * blo(w1.x), s0 * bhi(w0.x) + s1 * bhi(w1.x), s0 * blo(w0.y) + s1 * blo(w1.y), s0 * bhi(w0.y) + s1 * bhi(w1.y),
                      s0 * blo(w0.z) + s1 * blo(w1.z), s0 * bhi(w0.z) + s1 * bhi(w1.z), s0 * blo(w0.w) + s1 * blo(w1.w), s0 * bhi(w0.w) + s1 * bhi(w1.w)};
        float r = xreduce8(a, lane);
        r += __shfl_xor_sync(~0u, r, 1);
        if ((lane & 3) == 0) sts32(sb + OFF_RED + ((lane >> 2) * 8 + wid) * 4, __float_as_uint(r));
        bar_sync(B_CONS, 256);
        if (wid == 0) {
          const uint4 u = lds128(sb + OFF_RED + (lane & 7) * 32), w = lds128(sb + OFF_RED + (lane & 7) * 32 + 16);
          const float v0 = ((__uint_as_float(u.x) + __uint_as_float(u.y)) + (__uint_as_float(u.z) + __uint_as_float(u.w))) + ((__uint_as_float(w.x) + __uint_as_float(w.y)) + (__uint_as_float(w.z) + __uint_as_float(w.w)));
          const float v1 = __shfl_xor_sync(~0u, v0, 1);
          if ((lane & 1) == 0) st_ll(&scr->sync.modll[(lane >> 3) * 512 + b * 4 + ((lane & 7) >> 1)], pack2(v0, v1), tag);
        }
      }
      mbar_wait(XFULL(wid >> 1), 0);
      {
        float su[8], d0[8], d1[8];
#pragma unroll
        for (int i = 0; i < 8; i++) { su[i] = 0.f; d0[i] = 0.f; d1[i] = 0.f; }
#pragma unroll 1
        for (int sl = 0; sl < 8; sl++) {
          uint32_t a[16];
#pragma unroll
          for (int kk = 0; kk < 4; kk++) ldsm4(frag_addr(0, kk) + sl * HALF, a[4 * kk], a[4 * kk + 1], a[4 * kk + 2], a[4 * kk + 3]);
#pragma unroll
          for (int kk = 0; kk < 4; kk++) {
            const int o = (kk & 1) * 4;
            mma16816(su[o], su[o + 1], su[o + 2], su[o + 3], a[4 * kk], a[4 * kk + 1], a[4 * kk + 2], a[4 * kk + 3], 0x3f803f80u, 0x3f803f80u);
            mma16816(d0[o], d0[o + 1], d0[o + 2], d0[o + 3], a[4 * kk], a[4 * kk + 1], a[4 * kk + 2], a[4 * kk + 3], a[4 * kk], a[4 * kk + 2]);
            mma16816(d1[o], d1[o + 1], d1[o + 2], d1[o + 3], a[4 * kk], a[4 * kk + 1], a[4 * kk + 2], a[4 * kk + 3], a[4 * kk + 1], a[4 * kk + 3]);
          }
        }
        su[0] += su[4]; su[2] += su[6]; d0[0] += d0[4]; d0[1] += d0[5]; d1[2] += d1[6]; d1[3] += d1[7];
        const bool odd = lane & 4;
        const int src = (lane & 7) * 4 + ((lane & 7) >> 1);
        const float qa = __shfl_sync(~0u, odd ? d0[1] : d0[0], src), qb = __shfl_sync(~0u, odd ? d1[3] : d1[2], src);
        const float sa = __shfl_sync(~0u, su[0], src), sc = __shfl_sync(~0u, su[2], src);
        const float mean = ((lane & 8) ? sc : sa) * (1.f / DM);
        const float r = ln_rstd(mean, ((lane & 8) ? qb : qa) * (1.f / DM));
        nm = pack2(-mean, -mean); rhl = pack2(r, r - bround(r));
      }
      mbar_wait(MODFULL, 0);
    }

    const uint32_t dA0 = make_desc(sb + cw * 8192, 16);
    const uint32_t dB0 = make_desc(sb, 4096);
    uint32_t q[32];

    {
      {
        const uint4 s0 = lds128(sb + OFF_MODSM + lane * 16), s1 = lds128(sb + OFF_MODSM + 512 + lane * 16);
        const uint4 g0 = lds128(sb + OFF_MODSM + 1024 + lane * 16), g1 = lds128(sb + OFF_MODSM + 1536 + lane * 16);
        const uint32_t xad = sb + (lane >> 3) * HALF + wid * 2048 + ((lane & 7) << 4);
#pragma unroll 1
        for (int i = 0; i < 16; i += 2) {
          uint4 u[2], w[2];
          uint32_t r[2], m[2];
#pragma unroll
          for (int c = 0; c < 2; c++) {
            const uint32_t ad = (xad ^ (((i + c) & 7) << 4)) + (i + c) * 128;
            u[c] = lds128(ad); w[c] = lds128(ad + 65536);
            r[c] = __shfl_sync(~0u, rhl, i + c); m[c] = __shfl_sync(~0u, nm, i + c);
          }
#pragma unroll
          for (int c = 0; c < 2; c++) {
            const uint32_t ad = (xad ^ (((i + c) & 7) << 4)) + (i + c) * 128;
            const uint32_t rh = __byte_perm(r[c], 0, 0x1010), rl = __byte_perm(r[c], 0, 0x3232);
            auto nrm = [&](uint32_t xv, uint32_t gw, uint32_t sw) { const uint32_t d = hfma2(xv, 0x3f803f80u, m[c]); return hfma2(hfma2(d, rh, hfma2(d, rl, 0x80008000u)), gw, sw); };
            u[c].x = nrm(u[c].x, g0.x, s0.x); u[c].y = nrm(u[c].y, g0.y, s0.y); u[c].z = nrm(u[c].z, g0.z, s0.z); u[c].w = nrm(u[c].w, g0.w, s0.w);
            w[c].x = nrm(w[c].x, g1.x, s1.x); w[c].y = nrm(w[c].y, g1.y, s1.y); w[c].z = nrm(w[c].z, g1.z, s1.z); w[c].w = nrm(w[c].w, g1.w, s1.w);
            sts128(ad, u[c].x, u[c].y, u[c].z, u[c].w);
            sts128(ad + 65536, w[c].x, w[c].y, w[c].z, w[c].w);
          }
        }
      }
      fence_async_smem();
      bar_sync(B_WG + cw, 128);
      uint32_t held[64];
      float acc[128];
      int h6 = 8, prev = 8;
#pragma unroll 1
      for (int pass = 0; pass < 2; pass++) {
#pragma unroll 1
        for (int k = 0; k < 16; k++) {
          if (pass == 0 && cw == 1 && k == 8) bar_sync(B_LAG, 256);
          wait_full(h6);
          wg_fence();
#pragma unroll
          for (int ks = 0; ks < 2; ks++) wgmma_ss_n256_t1(acc, dA0 + (k >> 1) * 1024 + (k & 1) * 4 + ks * 2, dB0 + h6 * 1024 + ks * 128, (k | ks) != 0);
          wg_commit();
          if (pass == 0 && cw == 0 && k == 8 + LAG) bar_arrive(B_LAG, 256);
          if (k > 0) {
            wg_wait<1>();
            if (pass == 0 || k < 11) release(prev); else if (prev & 1) release_a(prev >> 1);
          }
          prev = h6; h6 = h6 == 13 ? 8 : h6 + 1;
        }
        wg_wait<0>(); pin(acc);
        release(pass ? 19 : prev);
        if (pass == 0) {
#pragma unroll
          for (int j = 0; j < 64; j++) held[j] = pack2(acc[2 * j], acc[2 * j + 1]);
          pin(held);
        }
      }
#pragma unroll
      for (int j = 0; j < 32; j++) q[j] = pack2(acc[2 * j], acc[2 * j + 1]);
#pragma unroll
      for (int kk = 0; kk < 8; kk++) {
        stsm4(frag_addr(0, kk), pack2(acc[64 + 8 * kk], acc[65 + 8 * kk]), pack2(acc[66 + 8 * kk], acc[67 + 8 * kk]), pack2(acc[68 + 8 * kk], acc[69 + 8 * kk]), pack2(acc[70 + 8 * kk], acc[71 + 8 * kk]));
        stsm4(frag_addr(1, kk), held[4 * kk], held[4 * kk + 1], held[4 * kk + 2], held[4 * kk + 3]);
        stsm4(frag_addr(2, kk), held[32 + 4 * kk], held[33 + 4 * kk], held[34 + 4 * kk], held[35 + 4 * kk]);
      }
      pin(q);
    }

    {
      const float cl2 = 0.08838834764831845f * 1.4426950408889634f;
      const uint64_t dK0 = make_desc(sb + 5 * SLOT, 16) | 0x4000004000000000ull;
      const uint64_t dV0 = make_desc(sb + 3 * SLOT, 16384) | 0x4000004000000000ull;
      float o[64], s[64];
      uint32_t p[32];
      float ms0 = 0.f, ms1 = 0.f, l0 = 1.f, l1 = 1.f, t0, t1;
      auto qk = [&](int st) {
#pragma unroll
        for (int kk = 0; kk < 8; kk++) wgmma64_rs_n128_t0(s, q[4 * kk], q[4 * kk + 1], q[4 * kk + 2], q[4 * kk + 3], dK0 + st * 2048 + (kk >> 2) * 1024 + (kk & 3) * 2, kk != 0);
        wg_commit();
      };
      auto pv = [&](int st, int acc) {
#pragma unroll
        for (int kk = 0; kk < 8; kk++) wgmma64_rs_n128_t1(o, p[4 * kk], p[4 * kk + 1], p[4 * kk + 2], p[4 * kk + 3], dV0 + st * 2048 + kk * 128, (kk != 0) | acc);
        wg_commit();
      };
      auto rowmax = [&](float& a, float& c) {
        int u[2], w[2];
#pragma unroll
        for (int j = 0; j < 16; j++) {
          const int e0 = __float_as_int(s[4 * j]), e1 = __float_as_int(s[4 * j + 1]), e2 = __float_as_int(s[4 * j + 2]), e3 = __float_as_int(s[4 * j + 3]);
          u[j & 1] = j < 2 ? max(e0, e1) : __vimax3_s32(e0, e1, u[j & 1]); w[j & 1] = j < 2 ? max(e2, e3) : __vimax3_s32(e2, e3, w[j & 1]);
        }
        float x0 = __int_as_float(max(u[0], u[1])), x1 = __int_as_float(max(w[0], w[1]));
        x0 = fmaxf(x0, __shfl_xor_sync(~0u, x0, 1)); x1 = fmaxf(x1, __shfl_xor_sync(~0u, x1, 1));
        x0 = fmaxf(x0, __shfl_xor_sync(~0u, x0, 2)); x1 = fmaxf(x1, __shfl_xor_sync(~0u, x1, 2));
        a = fmaf(x0, cl2, BIAS); c = fmaf(x1, cl2, BIAS);
      };
      auto exprange = [&](auto j0, auto j1) {
#pragma unroll
        for (int j = j0; j < j1; j++) {
          s[4 * j] = ex2(fmaf(s[4 * j], cl2, -ms0)); s[4 * j + 1] = ex2(fmaf(s[4 * j + 1], cl2, -ms0));
          s[4 * j + 2] = ex2(fmaf(s[4 * j + 2], cl2, -ms1)); s[4 * j + 3] = ex2(fmaf(s[4 * j + 3], cl2, -ms1));
          if (j == 0) { t0 = s[0] + s[1]; t1 = s[2] + s[3]; } else { t0 += s[4 * j] + s[4 * j + 1]; t1 += s[4 * j + 2] + s[4 * j + 3]; }
        }
      };
      auto cvtp = [&]() {
#pragma unroll
        for (int j = 0; j < 32; j++) p[j] = pack2(s[2 * j], s[2 * j + 1]);
      };
      auto inv_l = [&](float& i0, float& i1) {
        float a = l0 + __shfl_xor_sync(~0u, l0, 1), c = l1 + __shfl_xor_sync(~0u, l1, 1);
        a += __shfl_xor_sync(~0u, a, 2); c += __shfl_xor_sync(~0u, c, 2);
        i0 = rcp_fast(a); i1 = rcp_fast(c);
      };
      if (cw == 0) bar_arrive(B_PP, 256);
      mbar_wait(AFULL(5), 0);
      float i0 = 0.f, i1 = 0.f;
#pragma unroll 1
      for (int t = 0; t < 64; t++) {
        const int st = t & 1;
        bar_sync(B_PP + cw, 256);
        wg_fence();
        qk(st);
        if ((t & 15) == 0) inv_l(i0, i1);
        if ((t & 15) == 1 && t > 1) {
          const int slot = (t >> 4) - 1;
#pragma unroll
          for (int kk = 0; kk < 8; kk++) {
            const uint32_t w0 = pack2(o[8 * kk] * i0, o[8 * kk + 1] * i0), w1 = pack2(o[8 * kk + 2] * i1, o[8 * kk + 3] * i1);
            const uint32_t w2 = pack2(o[8 * kk + 4] * i0, o[8 * kk + 5] * i0), w3 = pack2(o[8 * kk + 6] * i1, o[8 * kk + 7] * i1);
            stsm4(frag_addr(slot, kk), w0, w1, w2, w3);
          }
        }
        mbar_wait(AFULL(3 + st), t >> 1);
        wg_fence();
        pv(st, (t & 15) != 1);
        bar_arrive(B_PP + (cw ^ 1), 256);
        const bool first = (t & 15) == 0;
        wg_wait<1>(); pin(s);
        release_a(5 + st);
        if (first) { rowmax(ms0, ms1); l0 = 0.f; l1 = 0.f; }
        exprange(IC<0>(), IC<EXP_SPLIT>());
        pin(s);
        mbar_wait_hot(AFULL(6 - st), (t + 1) >> 1);
        wg_wait<0>(); pin(o); pin(p);
        release_a(3 + st);
        exprange(IC<EXP_SPLIT>(), IC<16>());
        cvtp();
        if (__any_sync(~0u, !(t0 + t1 <= REDO_SUM))) {
          RedoArgs r;
#pragma unroll
          for (int j = 0; j < 16; j++) r.o[j] = make_float4(o[4 * j], o[4 * j + 1], o[4 * j + 2], o[4 * j + 3]);
#pragma unroll
          for (int kk = 0; kk < 8; kk++) r.qp[kk] = make_uint4(q[4 * kk], q[4 * kk + 1], q[4 * kk + 2], q[4 * kk + 3]);
          r.ml = make_float4(ms0, ms1, l0, l1);
          const float2 ts = redo_tile(r, kc, g * 16 + (t & 15));
          ms0 = r.ml.x; ms1 = r.ml.y; l0 = r.ml.z; l1 = r.ml.w; t0 = ts.x; t1 = ts.y;
#pragma unroll
          for (int j = 0; j < 16; j++) { o[4 * j] = r.o[j].x; o[4 * j + 1] = r.o[j].y; o[4 * j + 2] = r.o[j].z; o[4 * j + 3] = r.o[j].w; }
#pragma unroll
          for (int kk = 0; kk < 8; kk++) { p[4 * kk] = r.qp[kk].x; p[4 * kk + 1] = r.qp[kk].y; p[4 * kk + 2] = r.qp[kk].z; p[4 * kk + 3] = r.qp[kk].w; }
        }
        l0 += t0; l1 += t1;
        if ((t & 15) == 15 && t < 63) {
#pragma unroll
          for (int kk = 0; kk < 8; kk++) ldsm4(frag_addr(t >> 4, kk), q[4 * kk], q[4 * kk + 1], q[4 * kk + 2], q[4 * kk + 3]);
        }
        pin(p); pin(o); pin(q);
        asm volatile("" : "+f"(l0), "+f"(l1) :: "memory");
      }
      mbar_wait(AFULL(3), 0);
      if (cw == 0) bar_sync(B_PP, 256);
      wg_fence();
      pv(0, 1);
      inv_l(i0, i1);
      fence_async_smem();
      bar_sync(B_WG + cw, 128);
      wg_wait<0>(); pin(o);
      release_a(3);
#pragma unroll
      for (int j = 0; j < 16; j++) { q[2 * j] = pack2(o[4 * j] * i0, o[4 * j + 1] * i0); q[2 * j + 1] = pack2(o[4 * j + 2] * i1, o[4 * j + 3] * i1); }
      pin(q);
    }

    uint4* const part_w = scr->part + ((size_t)(rt * 8 + wid) * 16 + g) * 512 + lane;
    auto pack_part = [&](uint32_t (&w)[32], const float (&acc)[64]) {
#pragma unroll
      for (int j = 0; j < 32; j++) w[j] = pack2(acc[2 * j], acc[2 * j + 1]);
      pin(w);
    };
    auto store_part = [&](const uint32_t (&w)[32], int pass) { store_chunks<0>(part_w + (pass >> 1) * 4096 + (pass & 1) * 256, w); };
    auto add8 = [&](float* y, uint32_t ad) {
      const uint4 w = lds128(ad);
      y[0] += blo(w.x); y[1] += bhi(w.x); y[2] += blo(w.y); y[3] += bhi(w.y); y[4] += blo(w.z); y[5] += bhi(w.z); y[6] += blo(w.w); y[7] += bhi(w.w);
    };
    auto gather = [&](float* y, int tail) {
#pragma unroll
      for (int i = 0; i < 16; i++) y[i] = 0.f;
#pragma unroll 1
      for (int sg = 0; sg < 8; sg++) {
        const uint32_t ad = sb + tail * 65536 + sg * 8192 + wid * 512 + lane * 16;
        add8(y, ad); add8(y + 8, ad + 4096);
      }
    };
    auto late_vec = [&](uint32_t (&r)[8], auto which) {
      const uint4 u = ldg_cg128o<which.v * 1024>(&scr->sync.late[wid * 32 + (lane & 3) * 8]), w = ldg_cg128o<which.v * 1024 + 16>(&scr->sync.late[wid * 32 + (lane & 3) * 8]);
      r[0] = u.x; r[1] = u.y; r[2] = u.z; r[3] = u.w; r[4] = w.x; r[5] = w.y; r[6] = w.z; r[7] = w.w;
    };
    auto write_rows = [&](const uint32_t (&w)[16], __nv_bfloat16* dst) {
      const uint32_t st = sb + wid * 512;
      __syncwarp();
#pragma unroll
      for (int c = 0; c < 4; c++) stsm4(st + ((lane & 15) >> 2) * 4096 + (lane & 3) * 128 + (((c * 2 + (lane >> 4)) ^ (lane & 7)) << 4), w[4 * c], w[4 * c + 1], w[4 * c + 2], w[4 * c + 3]);
      __syncwarp();
      dst += (lane >> 3) * DM + (lane & 7) * 8;
      static_for<0, 4>([&](auto i) {
        const uint4 u = lds128(st + i * 4096 + (lane >> 3) * 128 + (((lane & 7) ^ ((i * 4 + (lane >> 3)) & 7)) << 4));
        stg128o<i.v * 8 * DM>(dst, u.x, u.y, u.z, u.w);
      });
    };

    {
      const uint32_t dO0 = make_desc(sb, 8192);
      float acc[64];
      uint32_t pk[32];
#pragma unroll 1
      for (int pass = 0; pass < 4; pass++) {
        int prev = 7;
#pragma unroll 1
        for (int k = 0; k < 6; k++) {
          const int h = (0x98dcba >> (k * 4)) & 15;
          wait_full(h);
          wg_fence();
#pragma unroll
          for (int ks = 0; ks < 4; ks++) wgmma_ss_n128_t1(acc, dA0 + k * 1024 + ks * 2, dO0 + h * 1024 + ks * 128, (k | ks) != 0);
          wg_commit();
          if (k > 0) { wg_wait<1>(); release(prev); }
          else if (pass > 0) {
            store_part(pk, pass - 1);
            if (pass == 2) bar_arrive(B_PUB, 320);
          }
          if (k == 4 && pass == 3) bar_arrive(B_X, 288);
          prev = h;
        }
#pragma unroll
        for (int k = 0; k < 2; k++) {
          wait_full(6 + k);
          wg_fence();
#pragma unroll
          for (int ks = 0; ks < 4; ks++) wgmma_rs_n128_t1(acc, q[16 * k + 4 * ks], q[16 * k + 4 * ks + 1], q[16 * k + 4 * ks + 2], q[16 * k + 4 * ks + 3], dO0 + (6 + k) * 1024 + ks * 128, 1);
          wg_commit();
          if (k == 0) { wg_wait<1>(); release(9); }
        }
        wg_wait<0>(); pin(acc); pin(q);
        if (pass < 3) { release(6); release(7); }
        pack_part(pk, acc);
      }
      store_part(pk, 3);
      bar_arrive(B_PUB + 1, 320);
    }

    uint32_t x1[16];
    {
      uint32_t ga[8], cb[8], sbv[8];
      const uint32_t* xp = (const uint32_t*)(x + (size_t)(rt * 128 + g * 16 + (lane >> 2)) * DM) + wid * 8 + (lane & 3);
#pragma unroll
      for (int j = 0; j < 8; j++) { x1[2 * j] = ldg_nc32(xp + 64 * (j >> 1) + 4 * (j & 1)); x1[2 * j + 1] = ldg_nc32(xp + 8 * (DM / 2) + 64 * (j >> 1) + 4 * (j & 1)); }
      wait_full(0);
      late_vec(ga, IC<0>()); late_vec(sbv, IC<1>()); late_vec(cb, IC<2>());
      float y[32];
      float s0 = 0.f, q0 = 0.f, s1 = 0.f, q1 = 0.f;
      auto resid = [&](auto j0, auto j1) {
#pragma unroll
        for (int j = j0; j < j1; j++) {
          y[4 * j] = fmaf(blo(ga[j]), y[4 * j], blo(x1[2 * j])); y[4 * j + 1] = fmaf(bhi(ga[j]), y[4 * j + 1], bhi(x1[2 * j]));
          y[4 * j + 2] = fmaf(blo(ga[j]), y[4 * j + 2], blo(x1[2 * j + 1])); y[4 * j + 3] = fmaf(bhi(ga[j]), y[4 * j + 3], bhi(x1[2 * j + 1]));
          x1[2 * j] = pack2(y[4 * j], y[4 * j + 1]); x1[2 * j + 1] = pack2(y[4 * j + 2], y[4 * j + 3]);
          s0 += y[4 * j] + y[4 * j + 1]; q0 = fmaf(y[4 * j], y[4 * j], q0); q0 = fmaf(y[4 * j + 1], y[4 * j + 1], q0);
          s1 += y[4 * j + 2] + y[4 * j + 3]; q1 = fmaf(y[4 * j + 2], y[4 * j + 2], q1); q1 = fmaf(y[4 * j + 3], y[4 * j + 3], q1);
        }
      };
      gather(y, 0);
      resid(IC<0>(), IC<4>());
      mbar_wait(XFULL(0), 1);
      gather(y + 16, 1);
      resid(IC<4>(), IC<8>());
#pragma unroll
      for (int o = 1; o < 4; o <<= 1) { s0 += __shfl_xor_sync(~0u, s0, o); q0 += __shfl_xor_sync(~0u, q0, o); s1 += __shfl_xor_sync(~0u, s1, o); q1 += __shfl_xor_sync(~0u, q1, o); }
      if ((lane & 3) == 0) sts128(sb + OFF_MODSM + (wid * 8 + (lane >> 2)) * 16, __float_as_uint(s0), __float_as_uint(q0), __float_as_uint(s1), __float_as_uint(q1));
      bar_sync(B_CONS, 256);
      s0 = q0 = s1 = q1 = 0.f;
#pragma unroll
      for (int w = 0; w < 8; w++) { const uint4 u = lds128(sb + OFF_MODSM + (w * 8 + (lane >> 2)) * 16); s0 += __uint_as_float(u.x); q0 += __uint_as_float(u.y); s1 += __uint_as_float(u.z); q1 += __uint_as_float(u.w); }
      const float m0 = s0 * (1.f / DM), m1 = s1 * (1.f / DM);
      const float r0 = ln_rstd(m0, q0 * (1.f / DM)), r1 = ln_rstd(m1, q1 * (1.f / DM));
      const float n0 = -bround(m0) * r0, n1 = -bround(m1) * r1;
      uint32_t hw[16];
#pragma unroll
      for (int j = 0; j < 8; j++) {
        hw[2 * j] = hfma2(pack2(fmaf(y[4 * j], r0, n0), fmaf(y[4 * j + 1], r0, n0)), cb[j], sbv[j]);
        hw[2 * j + 1] = hfma2(pack2(fmaf(y[4 * j + 2], r1, n1), fmaf(y[4 * j + 3], r1, n1)), cb[j], sbv[j]);
      }
#pragma unroll
      for (int c = 0; c < 4; c++) stsm4(sb + (c * 2 + cw) * 2048 + (lane & 15) * 128 + ((((wid & 3) * 2 + (lane >> 4)) ^ (lane & 7)) << 4), hw[4 * c], hw[4 * c + 1], hw[4 * c + 2], hw[4 * c + 3]);
      fence_async_smem();
      bar_arrive(B_PUB, 320);
    }

    {
      uint4* const act_w = scr->act + rt * 28672 + g * 14 * 256 + wid * 64;
      int h6 = 10, prev = 10;
      const uint32_t dG0 = make_desc(sb, 2048);
      auto swiglu = [&](float a0, float a1, float b0, float b1) {
        const float h0 = 0.5f * (SWP ? b0 : a0), h1 = 0.5f * (SWP ? b1 : a1);
        const float m0 = h0 * (SWP ? a0 : b0), m1 = h1 * (SWP ? a1 : b1);
        return pack2(fmaf(m0, tanh_fast(h0), m0), fmaf(m1, tanh_fast(h1), m1));
      };
      {
        float acc[128];
#pragma unroll 1
        for (int k = 0; k < 16; k++) {
          if (cw == 1 && k == 0) bar_sync(B_LAG, 256);
          if ((k & 1) == 0) wait_full(k >> 1);
          wait_full(h6);
          wg_fence();
#pragma unroll
          for (int ks = 0; ks < 2; ks++) wgmma_ss_n256_t1(acc, dA0 + (k >> 1) * 1024 + (k & 1) * 4 + ks * 2, dG0 + h6 * 1024 + ks * 64, (k | ks) != 0, 0x80000020u);
          wg_commit();
          if (cw == 0 && k == LAG) bar_arrive(B_LAG, 256);
          if (k == 8)
            static_for<0, 4>([&](auto c) { stg128o<c.v * 4096>(scr->x1 + (rt * 8 + g) * 1024 + ct, x1[4 * c], x1[4 * c + 1], x1[4 * c + 2], x1[4 * c + 3]); });
          if (k > 0) { wg_wait<1>(); release(prev); }
          prev = h6; h6 = h6 == 13 ? 8 : h6 + 1;
        }
        wg_wait<0>(); pin(acc);
        release(prev);
        static_for<0, 8>([&](auto ks) {
          constexpr int a = (ks.v >> 1) * 32 + (ks.v & 1) * 8;
          stg128o<(ks.v >> 1) * 8192 + (ks.v & 1) * 512>(act_w + lane, swiglu(acc[a], acc[a + 1], acc[a + 16], acc[a + 17]), swiglu(acc[a + 2], acc[a + 3], acc[a + 18], acc[a + 19]),
                                 swiglu(acc[a + 4], acc[a + 5], acc[a + 20], acc[a + 21]), swiglu(acc[a + 6], acc[a + 7], acc[a + 22], acc[a + 23]));
        });
        bar_arrive(B_PUB + 1, 320);
      }
      {
        float acc[96];
#pragma unroll 1
        for (int k = 0; k < 16; k++) {
          wait_full(h6);
          wg_fence();
#pragma unroll
          for (int ks = 0; ks < 2; ks++) wgmma_ss_n192_t1(acc, dA0 + (k >> 1) * 1024 + (k & 1) * 4 + ks * 2, dG0 + h6 * 1024 + ks * 64, (k | ks) != 0, 0x80000020u);
          wg_commit();
          if (k > 0) { wg_wait<1>(); release(prev); if ((k & 1) == 0 && k < 14) release((k >> 1) - 1); }
          prev = h6; h6 = h6 == 13 ? 8 : h6 + 1;
        }
        wg_wait<0>(); pin(acc);
        release(prev);
        const uint32_t stg = sb + 6 * HALF + wid * 2048;
        static_for<0, 6>([&](auto ks) {
          constexpr int a = (ks.v >> 1) * 32 + (ks.v & 1) * 8;
          sts128(stg + (ks.v >> 2) * HALF + (ks.v & 3) * 512 + lane * 16, swiglu(acc[a], acc[a + 1], acc[a + 16], acc[a + 17]), swiglu(acc[a + 2], acc[a + 3], acc[a + 18], acc[a + 19]),
                 swiglu(acc[a + 4], acc[a + 5], acc[a + 20], acc[a + 21]), swiglu(acc[a + 6], acc[a + 7], acc[a + 22], acc[a + 23]));
        });
        fence_async_smem();
        __syncwarp();
        bulk_store_e(act_w + 4 * 512, stg, 1024); bulk_store_e(act_w + 5 * 512, stg + 1024, 1024); bulk_store_e(act_w + 6 * 512, stg + HALF, 1024);
        asm volatile("cp.async.bulk.commit_group;" ::: "memory");
      }
    }

    {
      float acc[64];
      uint32_t a0[16], a1[16];
      uint4 xv[4];
      uint2 gv[4];
      auto dstep = [&](uint32_t (&a)[16], int h, int accum) {
        wait_full(h); wait_full(h + 1);
#pragma unroll
        for (int ks = 0; ks < 4; ks++) { const uint4 u = lds128(sb + h * HALF + (ks >> 1) * HALF + wid * 1024 + (ks & 1) * 512 + lane * 16); a[4 * ks] = u.x; a[4 * ks + 1] = u.y; a[4 * ks + 2] = u.z; a[4 * ks + 3] = u.w; }
        wg_fence();
#pragma unroll
        for (int ks = 0; ks < 4; ks++) wgmma_rs_n128_t1(acc, a[4 * ks], a[4 * ks + 1], a[4 * ks + 2], a[4 * ks + 3], dB0 + h * 1024 + (ks >> 1) * 1024 + 512 + (ks & 1) * 128, ks | accum);
        wg_commit();
        wg_wait<1>();
      };
      auto dfree = [&](int h) { release(h); release(h + 1); };
      mbar_wait(FULL(0), pf & 1);
      static_for<0, 4>([&](auto c) {
        xv[c] = ldg_cg128o<c.v * 512>(scr->x1 + ((rtd * 8 + wid) * 32 + cbd * 8 + rank * 4) * 32 + lane);
        asm volatile("ld.global.cg.v2.b32 {%0, %1}, [%2 + %3];" : "=r"(gv[c].x), "=r"(gv[c].y) : "l"(&scr->sync.late[768 + rank * 128 + (lane & 3) * 8 + cbd * 2]), "n"(c.v * 128) : "memory");
      });
      int h = 0, pv = 0;
      auto next = [&]() { pv = h; h = h == 4 ? 8 : h == 12 ? 6 : h == 6 ? 0 : h + 2; };
#pragma unroll 1
      for (int it = 0; it < 7; it++) {
        dstep(a0, h, it);
        pin(a1);
        if (it == 0) { bulk_store_wait(); bar_arrive(B_PUB, 288); pv = 6; }
        if (it < 5) dfree(pv);
        next();
        dstep(a1, h, 1);
        pin(a0);
        if (it < 4) dfree(pv);
        next();
      }
      wg_wait<0>(); pin(acc); pin(a1);
      mbar_wait(EMPTY(0), 0);
      uint32_t rdst, rbar;
      asm("mapa.shared::cluster.u32 %0, %1, %2;" : "=r"(rdst) : "r"(sb + ct * 16), "r"(rank ^ 1));
      asm("mapa.shared::cluster.u32 %0, %1, %2;" : "=r"(rbar) : "r"(XFULL(1)), "r"(rank ^ 1));
#pragma unroll
      for (int c = 0; c < 4; c++) {
        asm volatile("st.async.weak.shared::cluster.mbarrier::complete_tx::bytes.v4.b32 [%0], {%1, %2, %3, %4}, [%5];"
                     :: "r"(rdst + c * 4096), "r"(pack2(acc[32 + 8 * c], acc[33 + 8 * c])), "r"(pack2(acc[34 + 8 * c], acc[35 + 8 * c])),
                        "r"(pack2(acc[36 + 8 * c], acc[37 + 8 * c])), "r"(pack2(acc[38 + 8 * c], acc[39 + 8 * c])), "r"(rbar) : "memory");
      }
      asm volatile("barrier.cluster.arrive.relaxed.aligned;" ::: "memory");
      if (b == 0 && ct == 0) scr->sync.epoch = tag;
      mbar_wait(XFULL(1), 1);
      uint32_t ow[16];
#pragma unroll
      for (int c = 0; c < 4; c++) {
        add8(acc + 8 * c, sb + c * 4096 + ct * 16);
        auto fin = [&](uint32_t gw, uint32_t xw, int a) { return pack2(fmaf(blo(gw), acc[a], blo(xw)), fmaf(bhi(gw), acc[a + 1], bhi(xw))); };
        ow[4 * c] = fin(gv[c].x, xv[c].x, 8 * c); ow[4 * c + 1] = fin(gv[c].x, xv[c].y, 8 * c + 2);
        ow[4 * c + 2] = fin(gv[c].y, xv[c].z, 8 * c + 4); ow[4 * c + 3] = fin(gv[c].y, xv[c].w, 8 * c + 6);
      }
      write_rows(ow, out + (size_t)(rtd * 128 + wid * 16) * DM + cbd * 128 + rank * 64);
    }
    asm volatile("barrier.cluster.wait.aligned;" ::: "memory");
  }
}

typedef CUresult (*EncodeFn)(CUtensorMap*, CUtensorMapDataType, cuuint32_t, void*, const cuuint64_t*, const cuuint64_t*, const cuuint32_t*, const cuuint32_t*,
                             CUtensorMapInterleave, CUtensorMapSwizzle, CUtensorMapL2promotion, CUtensorMapFloatOOBfill);

void make_map(EncodeFn fn, CUtensorMap* m, const void* p, uint64_t rows, uint64_t cols, uint32_t box_rows) {
  cuuint64_t dims[2] = {cols, rows};
  cuuint64_t strides[1] = {cols * 2};
  cuuint32_t box[2] = {64, box_rows};
  cuuint32_t es[2] = {1, 1};
  fn(m, CU_TENSOR_MAP_DATA_TYPE_BFLOAT16, 2, const_cast<void*>(p), dims, strides, box, es, CU_TENSOR_MAP_INTERLEAVE_NONE, CU_TENSOR_MAP_SWIZZLE_128B,
     CU_TENSOR_MAP_L2_PROMOTION_L2_128B, CU_TENSOR_MAP_FLOAT_OOB_FILL_NONE);
}

}

extern "C" void kernel_launch(void* const* d_in, const int* in_sizes, int n_in, void* d_out, int out_size) {
  (void)in_sizes; (void)n_in; (void)out_size;
  typedef const __nv_bfloat16* P;
  P x = (P)d_in[0], k = (P)d_in[1], v = (P)d_in[2], wq = (P)d_in[3], wo = (P)d_in[4];
  P wg = (P)d_in[6], wu = (P)d_in[7], wd = (P)d_in[8], c = (P)d_in[9], wmod = (P)d_in[10];
  static EncodeFn fn = nullptr;
  static Scratch* scr = nullptr;
  if (!fn) {
    void* p = nullptr;
    cudaDriverEntryPointQueryResult qr;
    cudaGetDriverEntryPoint("cuTensorMapEncodeTiled", &p, cudaEnableDefault, &qr);
    fn = (EncodeFn)p;
    cudaGetSymbolAddress((void**)&scr, g_scratch);
    cudaFuncSetAttribute(fused_kernel<false>, cudaFuncAttributeMaxDynamicSharedMemorySize, SMEM_BYTES);
    cudaFuncSetAttribute(fused_kernel<true>, cudaFuncAttributeMaxDynamicSharedMemorySize, SMEM_BYTES);
  }
  Maps mp;
  make_map(fn, &mp.wq, wq, 512, 4096, 32);
  make_map(fn, &mp.k, k, 8 * SEQ, DH, 128);
  make_map(fn, &mp.v, v, 8 * SEQ, DH, 128);
  make_map(fn, &mp.wo, wo, 4096, DM, 64);
  {
    P lo = wg < wu ? wg : wu, hi = wg < wu ? wu : wg;
    cuuint64_t dims[3] = {FF, DM, 2};
    cuuint64_t strides[2] = {FF * 2, (cuuint64_t)((const char*)hi - (const char*)lo)};
    cuuint32_t box[3] = {32, 32, 2};
    cuuint32_t es[3] = {1, 1, 1};
    fn(&mp.gu, CU_TENSOR_MAP_DATA_TYPE_BFLOAT16, 3, (void*)lo, dims, strides, box, es, CU_TENSOR_MAP_INTERLEAVE_NONE, CU_TENSOR_MAP_SWIZZLE_64B,
       CU_TENSOR_MAP_L2_PROMOTION_L2_128B, CU_TENSOR_MAP_FLOAT_OOB_FILL_NONE);
  }
  make_map(fn, &mp.wd, wd, FF, DM, 32);
  make_map(fn, &mp.x, x, SEQ, DM, 32);
  if (wu < wg) fused_kernel<true><<<128, 384, SMEM_BYTES>>>(scr, c, wmod, x, k, (__nv_bfloat16*)d_out, wo, wg, wu, wd, v, mp);
  else fused_kernel<false><<<128, 384, SMEM_BYTES>>>(scr, c, wmod, x, k, (__nv_bfloat16*)d_out, wo, wg, wu, wd, v, mp);
}
```
